```python
import torch

def _softmax(x, axis=-1):
    return torch.softmax(x, dim=axis)
def _gelu(x):
    return torch.nn.functional.gelu(x, approximate="tanh")
def _silu(x):
    return torch.nn.functional.silu(x)
def _sigmoid(x):
    return torch.sigmoid(x)
def _layernorm(x, axis=-1, eps=1e-5):
    m = x.mean(dim=axis, keepdim=True)
    v = x.var(dim=axis, keepdim=True, unbiased=False)
    return (x - m) / torch.sqrt(v + eps)
def _scatter_add(tgt, idx, src, axis=0):
    return tgt.clone().index_add_(axis, idx, src)
def _segment_sum(src, seg, n):
    out = torch.zeros((n,) + src.shape[1:], dtype=src.dtype)
    return out.index_add_(0, seg, src)
def _pad(x, pw):
    flat = tuple(v for pair in reversed(pw) for v in pair)
    return torch.nn.functional.pad(x, flat)

kernel_name = 'standalone__gqa_block_cached__decode'

def setup_inputs():

    _w = (lambda a: (lambda t: t.to(torch.bfloat16) if t.is_floating_point() else t)(torch.as_tensor(a)))
    B, Sq, D = 1, 1, 640
    Hq, Hkv, Sk, Dh = 32, 32, 8192, 192
    assert Hq % Hkv == 0, (Hq, Hkv)
    return {
        "x": _w((lambda *s: torch.randn(*s, dtype=torch.bfloat16) * 0.8)(B, Sq, D)),
        "k_cache": _w((lambda *s: torch.randn(*s, dtype=torch.bfloat16) * 0.8)(B, Hkv, Sk, Dh)),
        "v_cache": _w((lambda *s: torch.randn(*s, dtype=torch.bfloat16) * 0.05)(B, Hkv, Sk, Dh)),
        "wq": _w((lambda *s: torch.randn(*s, dtype=torch.bfloat16) * 0.8)(D, Hq * Dh) * (D ** -0.5)),
        "wo": _w((lambda *s: torch.randn(*s, dtype=torch.bfloat16) * 0.05)(Hq * Dh, D) * ((Hq * Dh) ** -0.5)),
    }

def reference(x, k_cache, v_cache, wq, wo):
    B, Sq, D = x.shape
    Hq, Dh = 32, 192
    Hkv = k_cache.shape[1]
    rep = Hq // Hkv
    q = (lambda x, *d: x.permute(*d))((x @ wq).reshape(B, Sq, Hq, Dh), 0, 2, 1, 3)
    k = (lambda x, n, axis: torch.repeat_interleave(x, n, dim=axis))(k_cache, rep, axis=1)
    v = (lambda x, n, axis: torch.repeat_interleave(x, n, dim=axis))(v_cache, rep, axis=1)
    scores = torch.einsum("bhqd,bhkd->bhqk", q, k) * (Dh ** -0.5)
    p = _softmax(scores, axis=-1)
    o = torch.einsum("bhqk,bhkd->bhqd", p, v)
    return (lambda x, *d: x.permute(*d))(o, 0, 2, 1, 3).reshape(B, Sq, Hq * Dh) @ wo
```

```cpp
#include <cuda_runtime.h>
#include <cuda.h>
#include <cuda_bf16.h>
#include <stdint.h>

namespace gqa {

constexpr int D_MODEL = 640;
constexpr int NH      = 32;
constexpr int SK      = 8192;
constexpr int DH      = 192;
constexpr int QCOLS   = NH * DH;
constexpr int SPLIT   = 4;
constexpr int NCTA    = NH * SPLIT;
constexpr int NCW     = 4;
constexpr int W_XCHG = NCW + 1, W_COUNT = NCW + 2, W_RED = NCW + 3;
constexpr int NTHREADS = (NCW + 5) * 32;
constexpr int TOK_CTA = SK / SPLIT;
constexpr int NTILE   = TOK_CTA / 64;
constexpr int ROWB    = DH * 2;
constexpr int GRP     = 16 * ROWB;
constexpr int SLOT    = NCW * GRP;
constexpr int NSLOT   = 8;
constexpr int XROWS   = D_MODEL / SPLIT;
constexpr int OROWS   = DH / SPLIT;
constexpr int WOB     = 16 * D_MODEL * 2;
constexpr int NRED    = D_MODEL / 8;
constexpr int IT_K = 3, IT_V = IT_K + NTILE, IT_O = IT_V + NTILE, IT_END = IT_O + 3;

#define WIN_HEAD 2
#define WIN_MID 8
#define PACE_FROM 48
#define PACE_DELTA 640
#define PACE_DELTA_O 384
#define PACE_STAG 1
#define PACE_CLAMP 32
#define HEAD_UNTIL 11

constexpr int SM_RING = 0;
constexpr int SM_BARS = SM_RING + NSLOT * SLOT;
constexpr int SM_P    = SM_BARS + 256;
constexpr int SM_RED  = SM_P + NCW * NTILE * 8 * 4;
constexpr int SM_ML   = SM_RED + NCW * DH * 4;
constexpr int SM_Q    = SM_ML + 64;
constexpr int SM_O    = SM_Q + DH * 2;
constexpr int SM_TOTAL = SM_O + OROWS * 2;
constexpr int B_CONS = 1, B_Q = 2, B_O = 3, B_LATE = 4, B_L = 5, B_F = 6;
#define LATE_TILE 27

constexpr unsigned SPIN_LIMIT = 1u << 24;

struct Scratch {
    float x2[NRED * NCTA * 8];
    float x1[NCTA * SPLIT * OROWS];
    float xm[NCTA * SPLIT * 8];
    float x0[NCTA * SPLIT * DH];
    unsigned landed;
};
__device__ __align__(128) Scratch g_scratch;

#define CK_DECL
#define CKS(i)
#define CKD(i, dep)
#define CK_DUMP(n)
#define TLD(i, dep) do { } while (0)
#define TL(i) do { } while (0)

__device__ __forceinline__ uint32_t smem_u32(const void* p) { return (uint32_t)__cvta_generic_to_shared(p); }

__device__ __forceinline__ void mbar_init(uint32_t bar, uint32_t cnt) {
    asm volatile("mbarrier.init.shared::cta.b64 [%0], %1;" :: "r"(bar), "r"(cnt) : "memory");
}
__device__ __forceinline__ void mbar_expect_tx(uint32_t bar, uint32_t bytes) {
    asm volatile("mbarrier.arrive.expect_tx.shared::cta.b64 _, [%0], %1;" :: "r"(bar), "r"(bytes) : "memory");
}
__device__ __forceinline__ void mbar_arrive(uint32_t bar) {
    asm volatile("mbarrier.arrive.shared::cta.b64 _, [%0];" :: "r"(bar) : "memory");
}
__device__ __forceinline__ bool mbar_try(uint32_t bar, uint32_t parity) {
    uint32_t ok;
    asm volatile("{\n.reg .pred p;\nmbarrier.try_wait.parity.shared::cta.b64 p, [%1], %2;\nselp.u32 %0, 1, 0, p;\n}"
                 : "=r"(ok) : "r"(bar), "r"(parity) : "memory");
    return ok;
}
__device__ __forceinline__ bool mbar_test(uint32_t bar, uint32_t parity) {
    uint32_t ok;
    asm volatile("{\n.reg .pred p;\nmbarrier.test_wait.parity.shared::cta.b64 p, [%1], %2;\nselp.u32 %0, 1, 0, p;\n}"
                 : "=r"(ok) : "r"(bar), "r"(parity) : "memory");
    return ok;
}
__device__ __forceinline__ void mbar_wait(uint32_t bar, uint32_t parity) {
    if (mbar_try(bar, parity)) return;
    unsigned spins = 0;
    while (!mbar_try(bar, parity)) if (++spins > SPIN_LIMIT) __trap();
}
__device__ __forceinline__ void bulk_load(uint32_t dst, const void* src, uint32_t bytes, uint32_t bar) {
    asm volatile("cp.async.bulk.shared::cluster.global.mbarrier::complete_tx::bytes [%0], [%1], %2, [%3];"
                 :: "r"(dst), "l"(src), "r"(bytes), "r"(bar) : "memory");
}
__device__ __forceinline__ void tma_2d(uint32_t dst, const CUtensorMap* tm, int c0, int c1, uint32_t bar) {
    asm volatile("cp.async.bulk.tensor.2d.shared::cluster.global.mbarrier::complete_tx::bytes [%0], [%1, {%3, %4}], [%2];"
                 :: "r"(dst), "l"(tm), "r"(bar), "r"(c0), "r"(c1) : "memory");
}
__device__ __forceinline__ void tma_3d(uint32_t dst, const CUtensorMap* tm, int c0, int c1, int c2, uint32_t bar) {
    asm volatile("cp.async.bulk.tensor.3d.shared::cluster.global.mbarrier::complete_tx::bytes [%0], [%1, {%3, %4, %5}], [%2];"
                 :: "r"(dst), "l"(tm), "r"(bar), "r"(c0), "r"(c1), "r"(c2) : "memory");
}
__device__ __forceinline__ void ldsm4(uint32_t (&a)[4], uint32_t addr) {
    asm volatile("ldmatrix.sync.aligned.m8n8.x4.shared.b16 {%0,%1,%2,%3}, [%4];"
                 : "=r"(a[0]), "=r"(a[1]), "=r"(a[2]), "=r"(a[3]) : "r"(addr) : "memory");
}
__device__ __forceinline__ void ldsm4t(uint32_t (&a)[4], uint32_t addr) {
    asm volatile("ldmatrix.sync.aligned.m8n8.x4.trans.shared.b16 {%0,%1,%2,%3}, [%4];"
                 : "=r"(a[0]), "=r"(a[1]), "=r"(a[2]), "=r"(a[3]) : "r"(addr) : "memory");
}
__device__ __forceinline__ void mma16816(float (&c)[4], const uint32_t (&a)[4], uint32_t b0, uint32_t b1) {
    asm volatile("mma.sync.aligned.m16n8k16.row.col.f32.bf16.bf16.f32 {%0,%1,%2,%3}, {%4,%5,%6,%7}, {%8,%9}, {%0,%1,%2,%3};"
                 : "+f"(c[0]), "+f"(c[1]), "+f"(c[2]), "+f"(c[3])
                 : "r"(a[0]), "r"(a[1]), "r"(a[2]), "r"(a[3]), "r"(b0), "r"(b1));
}
__device__ __forceinline__ void bar_sync(int id, int n) { asm volatile("bar.sync %0, %1;" :: "r"(id), "r"(n) : "memory"); }
__device__ __forceinline__ void bar_arrive(int id, int n) { asm volatile("bar.arrive %0, %1;" :: "r"(id), "r"(n) : "memory"); }

__device__ __forceinline__ uint32_t enc(float v) { uint32_t u = __float_as_uint(v); return u ? u : 0x80000000u; }
__device__ __forceinline__ void st_x(float* p, float v) {
    asm volatile("st.relaxed.gpu.global.b32 [%0], %1;" :: "l"(p), "r"(enc(v)) : "memory");
}
__device__ __forceinline__ void st_x4(float* p, float4 v) {
    asm volatile("st.relaxed.gpu.global.v4.b32 [%0], {%1,%2,%3,%4};"
                 :: "l"(p), "r"(enc(v.x)), "r"(enc(v.y)), "r"(enc(v.z)), "r"(enc(v.w)) : "memory");
}
__device__ __forceinline__ void st_x2(float* p, float a, float b) {
    asm volatile("st.relaxed.gpu.global.v2.b32 [%0], {%1,%2};" :: "l"(p), "r"(enc(a)), "r"(enc(b)) : "memory");
}
__device__ __forceinline__ void st_zero2(float* p) {
    asm volatile("st.relaxed.gpu.global.v2.b32 [%0], {%1,%1};" :: "l"(p), "r"(0) : "memory");
}
__device__ __forceinline__ void st_zero4(float* p) {
    asm volatile("st.relaxed.gpu.global.v4.b32 [%0], {%1,%1,%1,%1};" :: "l"(p), "r"(0) : "memory");
}
__device__ __forceinline__ uint4 ld_x4(const float* p) {
    uint4 v;
    asm volatile("ld.relaxed.gpu.global.v4.b32 {%0,%1,%2,%3}, [%4];" : "=r"(v.x), "=r"(v.y), "=r"(v.z), "=r"(v.w) : "l"(p) : "memory");
    return v;
}
__device__ __forceinline__ uint2 ld_x2(const float* p) {
    uint2 v;
    asm volatile("ld.relaxed.gpu.global.v2.b32 {%0,%1}, [%2];" : "=r"(v.x), "=r"(v.y) : "l"(p) : "memory");
    return v;
}
__device__ __forceinline__ uint32_t umin4(uint4 v) { return min(min(v.x, v.y), min(v.z, v.w)); }
__device__ __forceinline__ uint32_t umin2(uint2 v) { return min(v.x, v.y); }

__device__ __forceinline__ float bf16r(float v) { return __bfloat162float(__float2bfloat16_rn(v)); }
__device__ __forceinline__ uint32_t pack_bf16(float lo, float hi) {
    __nv_bfloat162 h = __floats2bfloat162_rn(lo, hi);
    return *reinterpret_cast<uint32_t*>(&h);
}
__device__ __forceinline__ float ex2(float v) { float r; asm("ex2.approx.ftz.f32 %0, %1;" : "=f"(r) : "f"(v)); return r; }

__device__ __forceinline__ void rowsum_group(float (&acc)[12][4], uint32_t slot, const uint32_t (&off)[4], uint32_t b0, uint32_t b1) {
#pragma unroll
    for (int s = 0; s < 3; s++) {
        uint32_t a[4][4];
#pragma unroll
        for (int j = 0; j < 4; j++) ldsm4t(a[j], slot + off[j] + s * 128);
#pragma unroll
        for (int j = 0; j < 4; j++) mma16816(acc[s * 4 + j], a[j], b0, b1);
    }
}
__device__ __forceinline__ void rowsum_finish(const float (&acc)[12][4], float* red, int lane) {
    const int g = lane >> 2, t = lane & 3;
    const int from = (lane & ~3) | ((t + 3) & 3);
#pragma unroll
    for (int s = 0; s < 3; s++) {
        float val[8];
#pragma unroll
        for (int j = 0; j < 4; j++) {
            val[2 * j]     = acc[s * 4 + j][0] + acc[s * 4 + ((j + 3) & 3)][3];
            val[2 * j + 1] = acc[s * 4 + j][1] + acc[s * 4 + j][2];
        }
        float nw[4];
#pragma unroll
        for (int v = 0; v < 4; v++) nw[v] = val[v] + __shfl_xor_sync(0xffffffffu, val[v + 4], 2);
#pragma unroll
        for (int v = 0; v < 2; v++) {
            float f = nw[v] + __shfl_sync(0xffffffffu, nw[v + 2], from);
            red[64 * s + 8 * (2 * t + v) + g] = f;
        }
    }
}

__global__ void __launch_bounds__(NTHREADS, 1)
gqa_decode_kernel(const __nv_bfloat16* __restrict__ kc, const __nv_bfloat16* __restrict__ vc,
                  const __nv_bfloat16* __restrict__ x, __nv_bfloat16* __restrict__ out, Scratch* __restrict__ sc,
                  const __grid_constant__ CUtensorMap tm_wq, const __grid_constant__ CUtensorMap tm_wo) {
    extern __shared__ __align__(1024) unsigned char smem[];
    const int tid = threadIdx.x, warp = tid >> 5, lane = tid & 31;
    const int cta = blockIdx.x, h = cta >> 2, r = cta & 3;
    const uint32_t ring = smem_u32(smem) + SM_RING;
    const uint32_t full = smem_u32(smem) + SM_BARS, empty = full + NSLOT * 8;
    const unsigned char* kp = reinterpret_cast<const unsigned char*>(kc) + (size_t)cta * (TOK_CTA * ROWB);

    TL(0);
    if (tid == 0) {
        mbar_init(full + 8 * IT_K, 1);
        mbar_init(full, 1);
        asm volatile("fence.mbarrier_init.release.cluster;" ::: "memory");
        asm volatile("prefetch.tensormap [%0];" :: "l"(&tm_wq) : "memory");
        mbar_expect_tx(full + 8 * IT_K, SLOT);
        bulk_load(ring + IT_K * SLOT, kp, SLOT, full + 8 * IT_K);
        mbar_expect_tx(full, XROWS * ROWB);
        tma_2d(ring, &tm_wq, h * DH, r * XROWS, full);
#pragma unroll
        for (int i = 1; i < NSLOT; i++) if (i != IT_K) mbar_init(full + 8 * i, 1);
#pragma unroll
        for (int i = 0; i < NSLOT; i++) mbar_init(empty + 8 * i, NCW + 1);
        asm volatile("fence.mbarrier_init.release.cluster;" ::: "memory");
        mbar_arrive(full + 8);
        mbar_arrive(full + 16);
    }
    __syncthreads();
    const float LOG2E = 1.4426950408889634f;
    const int g = lane >> 2, t = lane & 3;
    float* ml = reinterpret_cast<float*>(smem + SM_ML);

    if (warp == 0) {
        if (lane == 0) {
            const unsigned char* vp = reinterpret_cast<const unsigned char*>(vc) + (size_t)cta * (TOK_CTA * ROWB);
            asm volatile("prefetch.tensormap [%0];" :: "l"(&tm_wo) : "memory");
            int landed = 0;
#pragma unroll 1
            for (int it = IT_K + 1; it < IT_END; it++) {
                const int s = it & (NSLOT - 1);
                const int win = it < HEAD_UNTIL ? WIN_HEAD : WIN_MID;
                if (it - IT_K >= PACE_FROM) {
                    const int need = min(NCTA * (it - IT_K) + PACE_STAG * cta - (it < IT_O ? PACE_DELTA : PACE_DELTA_O), NCTA * 2 * NTILE - PACE_CLAMP);
                    unsigned spins = 0;
                    while (landed < need) {
                        asm volatile("ld.relaxed.gpu.global.b32 %0, [%1];" : "=r"(landed) : "l"(&sc->landed) : "memory");
                        if (++spins > SPIN_LIMIT) __trap();
                    }
                }
                if (win < NSLOT) {
                    int j = it - win;
                    if (j < IT_K) j = IT_K; else if (j == IT_K) j = 0;
                    mbar_wait(full + 8 * (j & (NSLOT - 1)), (j / NSLOT) & 1);
                }
                if (it >= NSLOT) mbar_wait(empty + 8 * s, ((it / NSLOT) & 1) ^ 1);
                if (it < IT_O) {
                    mbar_expect_tx(full + 8 * s, SLOT);
                    bulk_load(ring + s * SLOT, it < IT_V ? kp + (size_t)(it - IT_K) * SLOT : vp + (size_t)(it - IT_V) * SLOT, SLOT, full + 8 * s);
                } else {
                    mbar_expect_tx(full + 8 * s, WOB);
                    tma_3d(ring + s * SLOT, &tm_wo, 0, cta * OROWS + (it - IT_O) * 16, 0, full + 8 * s);
                    TL(16 + it - IT_O);
                }
            }
        }
        return;
    }

    if (warp == W_COUNT) {
        if (lane == 0) {
            mbar_arrive(empty);
            mbar_arrive(empty + 8);
            mbar_arrive(empty + 16);
        }
#pragma unroll 1
        for (int it = IT_K; it < IT_O; it++) {
            const int s = it & (NSLOT - 1);
            mbar_wait(full + 8 * s, (it / NSLOT) & 1);
            if (lane == 0) {
                asm volatile("red.relaxed.gpu.global.add.u32 [%0], 1;" :: "l"(&sc->landed) : "memory");
                mbar_arrive(empty + 8 * s);
            }
            if (it == IT_V + LATE_TILE) bar_arrive(B_LATE, cta < NRED ? 128 : 64);
        }
        return;
    }

    if (warp == W_XCHG) {
        {
            float* in = sc->x0 + cta * SPLIT * DH + 2 * lane;
            uint2 v[SPLIT][3];
            unsigned spins = 0, lo;
            do {
#pragma unroll
                for (int s = 0; s < SPLIT; s++)
#pragma unroll
                    for (int i = 0; i < 3; i++) v[s][i] = ld_x2(in + s * DH + i * 64);
                lo = 0xffffffffu;
#pragma unroll
                for (int s = 0; s < SPLIT; s++)
#pragma unroll
                    for (int i = 0; i < 3; i++) lo = min(lo, umin2(v[s][i]));
                if (++spins > SPIN_LIMIT) __trap();
            } while (lo == 0);
            uint32_t* qw = reinterpret_cast<uint32_t*>(smem + SM_Q);
#pragma unroll
            for (int i = 0; i < 3; i++) {
                float a = (__uint_as_float(v[0][i].x) + __uint_as_float(v[1][i].x)) + (__uint_as_float(v[2][i].x) + __uint_as_float(v[3][i].x));
                float b = (__uint_as_float(v[0][i].y) + __uint_as_float(v[1][i].y)) + (__uint_as_float(v[2][i].y) + __uint_as_float(v[3][i].y));
                qw[i * 32 + lane] = pack_bf16(a, b);
            }
            bar_arrive(B_Q, (NCW + 1) * 32);
#pragma unroll
            for (int s = 0; s < SPLIT; s++)
#pragma unroll
                for (int i = 0; i < 3; i++) st_zero2(in + s * DH + i * 64);
        }
        {
            bar_sync(B_L, (NCW + 1) * 32);
            const float m = fmaxf(fmaxf(ml[0], ml[1]), fmaxf(ml[2], ml[3]));
            const float l = (ml[4] + ml[5]) + (ml[6] + ml[7]);
            if (lane < 2 * SPLIT) st_x4(sc->xm + ((h * SPLIT + (lane >> 1)) * SPLIT + r) * 8 + (lane & 1) * 4, make_float4(m, l, m, l));
            float* in = sc->xm + (cta * SPLIT + (lane & 3)) * 8;
            uint2 v;
            unsigned spins = 0;
            do {
                v = ld_x2(in);
                if (++spins > SPIN_LIMIT) __trap();
            } while (umin2(v) == 0);
            __syncwarp();
            const float ms = __uint_as_float(v.x);
            float mm = fmaxf(ms, __shfl_xor_sync(0xffffffffu, ms, 1));
            mm = fmaxf(mm, __shfl_xor_sync(0xffffffffu, mm, 2));
            float ll = __uint_as_float(v.y) * ex2((ms - mm) * LOG2E);
            ll += __shfl_xor_sync(0xffffffffu, ll, 1);
            ll += __shfl_xor_sync(0xffffffffu, ll, 2);
            if (lane == 0) ml[8] = ex2((m - mm) * LOG2E) / ll;
            if (lane < 2 * SPLIT) st_zero4(sc->xm + cta * SPLIT * 8 + lane * 4);
            bar_arrive(B_F, (NCW + 1) * 32);
        }
        {
            bar_sync(B_LATE, cta < NRED ? 128 : 64);
            const int j = lane < 24 ? lane : 0;
            float* in = sc->x1 + cta * SPLIT * OROWS + 2 * j;
            uint2 v[SPLIT];
            unsigned spins = 0;
            do {
#pragma unroll
                for (int s = 0; s < SPLIT; s++) v[s] = ld_x2(in + s * OROWS);
                if (++spins > SPIN_LIMIT) __trap();
            } while (min(min(umin2(v[0]), umin2(v[1])), min(umin2(v[2]), umin2(v[3]))) == 0);
            const float a = (__uint_as_float(v[0].x) + __uint_as_float(v[1].x)) + (__uint_as_float(v[2].x) + __uint_as_float(v[3].x));
            const float b = (__uint_as_float(v[0].y) + __uint_as_float(v[1].y)) + (__uint_as_float(v[2].y) + __uint_as_float(v[3].y));
            if (lane < 24) reinterpret_cast<uint32_t*>(smem + SM_O)[(j >> 3) * 8 + (j & 3) * 2 + ((j >> 2) & 1)] = pack_bf16(a, b);
            bar_arrive(B_O, (NCW + 1) * 32);
            TL(14);
            if (lane < 24) {
#pragma unroll
                for (int s = 0; s < SPLIT; s++) st_zero2(in + s * OROWS);
            }
        }
        return;
    }

    if (warp >= W_RED) {
        if (cta >= NRED) return;
        const int wr = warp - W_RED;
        float* p = sc->x2 + (cta * NCTA + lane) * 8 + wr * 4;
        __nv_bfloat16* po = out + cta * 8 + wr * 4 + (lane >> 3);
        bar_sync(B_LATE, 128);
        uint4 v[4];
        unsigned spins = 0;
        do {
#pragma unroll
            for (int i = 0; i < 4; i++) v[i] = ld_x4(p + i * 32 * 8);
            if (++spins > SPIN_LIMIT) __trap();
        } while (min(min(umin4(v[0]), umin4(v[1])), min(umin4(v[2]), umin4(v[3]))) == 0);
        __syncwarp();
        TL(12);
        float s0 = (__uint_as_float(v[0].x) + __uint_as_float(v[1].x)) + (__uint_as_float(v[2].x) + __uint_as_float(v[3].x));
        float s1 = (__uint_as_float(v[0].y) + __uint_as_float(v[1].y)) + (__uint_as_float(v[2].y) + __uint_as_float(v[3].y));
        float s2 = (__uint_as_float(v[0].z) + __uint_as_float(v[1].z)) + (__uint_as_float(v[2].z) + __uint_as_float(v[3].z));
        float s3 = (__uint_as_float(v[0].w) + __uint_as_float(v[1].w)) + (__uint_as_float(v[2].w) + __uint_as_float(v[3].w));
        const bool up = lane & 16;
        float a0 = (up ? s2 : s0) + __shfl_xor_sync(0xffffffffu, up ? s0 : s2, 16);
        float a1 = (up ? s3 : s1) + __shfl_xor_sync(0xffffffffu, up ? s1 : s3, 16);
        const bool up2 = lane & 8;
        float b = (up2 ? a1 : a0) + __shfl_xor_sync(0xffffffffu, up2 ? a0 : a1, 8);
        b += __shfl_xor_sync(0xffffffffu, b, 4);
        b += __shfl_xor_sync(0xffffffffu, b, 2);
        b += __shfl_xor_sync(0xffffffffu, b, 1);
        if ((lane & 7) == 0) *po = __float2bfloat16_rn(b);
#pragma unroll
        for (int i = 0; i < 4; i++) st_zero4(p + i * 32 * 8);
        if (cta == 0 && tid == W_RED * 32) asm volatile("st.relaxed.gpu.global.b32 [%0], %1;" :: "l"(&sc->landed), "r"(0) : "memory");
        TL(13);
        return;
    }

    const int cw = warp - 1;
    const bool diag = (t == (g >> 1));
    const uint32_t sel0 = diag ? ((g & 1) ? 0x1044u : 0x4410u) : 0x4444u;
    const uint32_t sel1 = diag ? ((g & 1) ? 0x3244u : 0x4432u) : 0x4444u;
    uint32_t offk[4], offv[4];
    {
        const int mi = lane >> 3, rr = lane & 7;
#pragma unroll
        for (int j = 0; j < 4; j++) {
            offk[j] = cw * GRP + (rr + 8 * (mi & 1)) * ROWB + ((2 * j + (mi >> 1) + rr) & 7) * 16;
            offv[j] = cw * GRP + (rr + 8 * (mi >> 1)) * ROWB + ((2 * j + (mi & 1) + rr) & 7) * 16;
        }
    }
    float* red = reinterpret_cast<float*>(smem + SM_RED);
    uint32_t* pw = reinterpret_cast<uint32_t*>(smem + SM_P) + cw * (NTILE * 8);
    auto release = [&](int s) { __syncwarp(); if (lane == 0) mbar_arrive(empty + 8 * s); };

    float acc[12][4];
    {
        const int nq = cw < 2 ? 3 : 2;
        uint32_t xw[3];
#pragma unroll
        for (int i = 0; i < 3; i++) {
            xw[i] = 0;
            if (i < nq) {
                const unsigned short* xs = reinterpret_cast<const unsigned short*>(x) + r * XROWS + (cw + 4 * i) * 16 + g;
                xw[i] = (uint32_t)__ldg(xs) | ((uint32_t)__ldg(xs + 8) << 16);
            }
        }
#pragma unroll
        for (int i = 0; i < 12; i++) { acc[i][0] = acc[i][1] = acc[i][2] = acc[i][3] = 0.f; }
        mbar_wait(full, 0);
        TL(1);
#pragma unroll 1
        for (int i = 0; i < 3; i++) {
            const uint32_t w = i == 0 ? xw[0] : (i == 1 ? xw[1] : xw[2]);
            if (i < nq) rowsum_group(acc, ring + i * SLOT, offv, __byte_perm(w, 0, sel0), __byte_perm(w, 0, sel1));
            release(i);
        }
        TL(2);
        rowsum_finish(acc, red + cw * DH, lane);
        bar_sync(B_CONS, NCW * 32);
        const float2* r2 = reinterpret_cast<const float2*>(red);
        float* dst = sc->x0 + ((h * SPLIT + cw) * SPLIT + r) * DH + 2 * lane;
#pragma unroll
        for (int i = 0; i < 3; i++) {
            const float2 a = r2[i * 32 + lane], b = r2[DH / 2 + i * 32 + lane], c = r2[DH + i * 32 + lane], d = r2[3 * DH / 2 + i * 32 + lane];
            st_x2(dst + i * 64, (a.x + b.x) + (c.x + d.x), (a.y + b.y) + (c.y + d.y));
        }
        bar_sync(B_Q, (NCW + 1) * 32);
    }

    float mx = -INFINITY;
    {
        const uint32_t* qw = reinterpret_cast<const uint32_t*>(smem + SM_Q);
        uint32_t qb[3][8];
#pragma unroll
        for (int s = 0; s < 3; s++)
#pragma unroll
            for (int u = 0; u < 8; u++) qb[s][u] = qw[32 * s + 4 * ((u + g) & 7) + t];
        TL(3);
        const float scale = 0.07216878364870322f;
#pragma unroll 1
        for (int i = 0; i < NTILE; i++) {
            const int it = IT_K + i, slot = it & (NSLOT - 1);
            mbar_wait(full + 8 * slot, (it / NSLOT) & 1);
            const uint32_t sa = ring + slot * SLOT;
            float c[3][4];
#pragma unroll
            for (int s = 0; s < 3; s++) {
                uint32_t a[4][4];
                c[s][0] = c[s][1] = c[s][2] = c[s][3] = 0.f;
#pragma unroll
                for (int j = 0; j < 4; j++) ldsm4(a[j], sa + offk[j] + s * 128);
#pragma unroll
                for (int j = 0; j < 4; j++) mma16816(c[s], a[j], qb[s][2 * j], qb[s][2 * j + 1]);
            }
            release(slot);
            const bool odd = g & 1;
            float lo = odd ? (c[0][1] + c[1][1]) + c[2][1] : (c[0][0] + c[1][0]) + c[2][0];
            float hi = odd ? (c[0][3] + c[1][3]) + c[2][3] : (c[0][2] + c[1][2]) + c[2][2];
            lo = bf16r(bf16r(lo) * scale);
            hi = bf16r(bf16r(hi) * scale);
            if (diag) {
                mx = fmaxf(mx, fmaxf(lo, hi));
                pw[i * 8 + g] = pack_bf16(lo, hi);
            }
        }
    }
    TL(4);
    {
#pragma unroll
        for (int o = 16; o > 0; o >>= 1) mx = fmaxf(mx, __shfl_xor_sync(0xffffffffu, mx, o));
        if (lane == 0) ml[cw] = mx;
        bar_sync(B_CONS, NCW * 32);
        mx = fmaxf(fmaxf(ml[0], ml[1]), fmaxf(ml[2], ml[3]));
        float lsum = 0.f;
#pragma unroll
        for (int i = 0; i < NTILE * 8 / 32; i++) {
            uint32_t w = pw[i * 32 + lane];
            float e0 = ex2((__uint_as_float(w << 16) - mx) * LOG2E);
            float e1 = ex2((__uint_as_float(w & 0xffff0000u) - mx) * LOG2E);
            lsum += e0 + e1;
            pw[i * 32 + lane] = pack_bf16(e0, e1);
        }
#pragma unroll
        for (int o = 16; o > 0; o >>= 1) lsum += __shfl_xor_sync(0xffffffffu, lsum, o);
        if (lane == 0) ml[4 + cw] = lsum;
        __syncwarp();
        bar_arrive(B_L, (NCW + 1) * 32);
    }
    TL(5);
#pragma unroll
    for (int i = 0; i < 12; i++) { acc[i][0] = acc[i][1] = acc[i][2] = acc[i][3] = 0.f; }
#pragma unroll 1
    for (int i = 0; i < NTILE; i++) {
        const int it = IT_V + i, slot = it & (NSLOT - 1);
        const uint32_t w = pw[i * 8 + g];
        mbar_wait(full + 8 * slot, (it / NSLOT) & 1);
        rowsum_group(acc, ring + slot * SLOT, offv, __byte_perm(w, 0, sel0), __byte_perm(w, 0, sel1));
        release(slot);
    }
    TL(6);
    CK_DECL;
    CKS(0);
    rowsum_finish(acc, red + cw * DH, lane);
    CKS(1);
    bar_sync(B_F, (NCW + 1) * 32);
    if (lane < 12) {
        const float f = ml[8];
        const float4* r4 = reinterpret_cast<const float4*>(red) + cw * 12 + lane;
        const float4 a = r4[0], b = r4[DH / 4], c = r4[2 * DH / 4], d = r4[3 * DH / 4];
        st_x4(sc->x1 + ((h * SPLIT + cw) * SPLIT + r) * OROWS + lane * 4,
              make_float4(((a.x + b.x) + (c.x + d.x)) * f, ((a.y + b.y) + (c.y + d.y)) * f,
                          ((a.z + b.z) + (c.z + d.z)) * f, ((a.w + b.w) + (c.w + d.w)) * f));
    }
    __syncwarp();
    CKS(2);
    TL(7);
    {
        uint32_t offw[10];
        {
            const int rr = lane & 7, mi = lane >> 3;
#pragma unroll
            for (int b = 0; b < 10; b++) {
                const int B = cw * 10 + b;
                offw[b] = ring + (B >> 2) * 2048 + (rr + 8 * (mi >> 1)) * 128 + (((2 * (B & 3) + (mi & 1)) ^ rr) * 16);
            }
        }
        float* dst = sc->x2 + ((cw * 20 + t) * NCTA + cta) * 8 + g;
        constexpr int S0 = IT_O & (NSLOT - 1), S1 = (IT_O + 1) & (NSLOT - 1), S2 = (IT_O + 2) & (NSLOT - 1);
        constexpr int P0 = (IT_O / NSLOT) & 1, P1 = ((IT_O + 1) / NSLOT) & 1, P2 = ((IT_O + 2) / NSLOT) & 1;
        uint32_t a0[10][4], a1[10][4], a2[10][4];
        mbar_wait(full + 8 * S0, P0);
#pragma unroll
        for (int b = 0; b < 10; b++) ldsm4t(a0[b], offw[b] + S0 * SLOT);
        mbar_wait(full + 8 * S1, P1);
#pragma unroll
        for (int b = 0; b < 10; b++) ldsm4t(a1[b], offw[b] + S1 * SLOT);
        CKS(3);
        bar_sync(B_O, (NCW + 1) * 32);
        uint2 ob[3];
#pragma unroll
        for (int ks = 0; ks < 3; ks++) ob[ks] = reinterpret_cast<const uint2*>(smem + SM_O)[ks * 4 + t];
        const bool early = __all_sync(0xffffffffu, mbar_test(full + 8 * S2, P2));
        CKD(4, ob[0].x ^ ob[1].x ^ ob[2].x);
        TL(8);
        float y[10][4];
#pragma unroll
        for (int b = 0; b < 10; b++) { y[b][0] = y[b][1] = y[b][2] = y[b][3] = 0.f; }
        if (early) {
#pragma unroll
            for (int b = 0; b < 10; b++) ldsm4t(a2[b], offw[b] + S2 * SLOT);
        }
#pragma unroll
        for (int b = 0; b < 10; b++) mma16816(y[b], a0[b], ob[0].x, ob[0].y);
#pragma unroll
        for (int b = 0; b < 10; b++) mma16816(y[b], a1[b], ob[1].x, ob[1].y);
        CKS(5);
        if (!early) {
            mbar_wait(full + 8 * S2, P2);
            TL(9);
#pragma unroll
            for (int b = 0; b < 10; b++) ldsm4t(a2[b], offw[b] + S2 * SLOT);
        }
        CKS(6);
#pragma unroll
        for (int b = 0; b < 10; b++) mma16816(y[b], a2[b], ob[2].x, ob[2].y);
        CKS(7);
#pragma unroll
        for (int i = 0; i < 5; i++) {
            const float v = (t & 2) ? ((t & 1) ? y[2 * i + 1][2] : y[2 * i + 1][0]) : ((t & 1) ? y[2 * i][2] : y[2 * i][0]);
            st_x(dst + i * 4 * NCTA * 8, v);
        }
        CKS(8); CKS(9); CKS(10);
        TL(10);
        CK_DUMP(11);
    }
}

typedef CUresult (*EncodeTiledFn)(CUtensorMap*, CUtensorMapDataType, cuuint32_t, void*, const cuuint64_t*, const cuuint64_t*,
                                  const cuuint32_t*, const cuuint32_t*, CUtensorMapInterleave, CUtensorMapSwizzle,
                                  CUtensorMapL2promotion, CUtensorMapFloatOOBfill);

}

extern "C" void kernel_launch(void* const* d_in, const int* in_sizes, int n_in, void* d_out, int out_size) {
    (void)in_sizes; (void)n_in; (void)out_size;
    using namespace gqa;
    static EncodeTiledFn encode = nullptr;
    static Scratch* scratch = nullptr;
    if (!encode) {
        cudaGetSymbolAddress((void**)&scratch, g_scratch);
        void* fn = nullptr;
        cudaDriverEntryPointQueryResult qr;
        cudaGetDriverEntryPoint("cuTensorMapEncodeTiled", &fn, cudaEnableDefault, &qr);
        encode = (EncodeTiledFn)fn;
        cudaFuncSetAttribute(gqa_decode_kernel, cudaFuncAttributeMaxDynamicSharedMemorySize, SM_TOTAL);
    }
    CUtensorMap tm_wq, tm_wo;
    {
        cuuint64_t dims[2] = {QCOLS, D_MODEL}, strides[1] = {QCOLS * 2};
        cuuint32_t box[2] = {DH, XROWS}, es[2] = {1, 1};
        encode(&tm_wq, CU_TENSOR_MAP_DATA_TYPE_BFLOAT16, 2, d_in[3], dims, strides, box, es, CU_TENSOR_MAP_INTERLEAVE_NONE,
               CU_TENSOR_MAP_SWIZZLE_NONE, CU_TENSOR_MAP_L2_PROMOTION_NONE, CU_TENSOR_MAP_FLOAT_OOB_FILL_NONE);
    }
    {
        cuuint64_t dims[3] = {64, QCOLS, D_MODEL / 64}, strides[2] = {D_MODEL * 2, 128};
        cuuint32_t box[3] = {64, 16, D_MODEL / 64}, es[3] = {1, 1, 1};
        encode(&tm_wo, CU_TENSOR_MAP_DATA_TYPE_BFLOAT16, 3, d_in[4], dims, strides, box, es, CU_TENSOR_MAP_INTERLEAVE_NONE,
               CU_TENSOR_MAP_SWIZZLE_128B, CU_TENSOR_MAP_L2_PROMOTION_NONE, CU_TENSOR_MAP_FLOAT_OOB_FILL_NONE);
    }
    gqa_decode_kernel<<<NCTA, NTHREADS, SM_TOTAL>>>((const __nv_bfloat16*)d_in[1], (const __nv_bfloat16*)d_in[2],
                                                    (const __nv_bfloat16*)d_in[0], (__nv_bfloat16*)d_out, scratch, tm_wq, tm_wo);
}
```

```cpp
#include <cuda_runtime.h>
#include <cuda.h>
#include <cuda_bf16.h>
#include <stdint.h>

namespace gqa {

constexpr int D_MODEL = 640;
constexpr int NH      = 32;
constexpr int SK      = 8192;
constexpr int DH      = 192;
constexpr int QCOLS   = NH * DH;
constexpr int SPLIT   = 4;
constexpr int NCTA    = NH * SPLIT;
constexpr int NCW     = 4;
constexpr int W_XCHG = NCW + 1, W_COUNT = NCW + 2, W_RED = NCW + 3;
#define NREDW 1
constexpr int NTHREADS = (NCW + 3 + NREDW) * 32;
constexpr int TOK_CTA = SK / SPLIT;
constexpr int NTILE   = TOK_CTA / 64;
constexpr int ROWB    = DH * 2;
constexpr int GRP     = 16 * ROWB;
constexpr int SLOT    = NCW * GRP;
constexpr int NSLOT   = 8;
constexpr int XROWS   = D_MODEL / SPLIT;
constexpr int OROWS   = DH / SPLIT;
constexpr int WOB     = 16 * D_MODEL * 2;
constexpr int NRED    = D_MODEL / 8;
constexpr int IT_K = 3, IT_V = IT_K + NTILE, IT_O = IT_V + NTILE, IT_END = IT_O + 3;

#define WIN_HEAD 3
#define WIN_MID 8
#define PACE_FROM 48
#define PACE_DELTA 640
#define PACE_D0 384
#define PACE_D1 256
#define PACE_D2 128
#define PACE_SO 4
#define PACE_STAG 1
#define PACE_CLAMP 32
#define HEAD_UNTIL 11

constexpr int SM_RING = 0;
constexpr int SM_BARS = SM_RING + NSLOT * SLOT;
constexpr int SM_P    = SM_BARS + 256;
constexpr int SM_RED  = SM_P + NCW * NTILE * 8 * 4;
constexpr int SM_ML   = SM_RED + NCW * DH * 4;
constexpr int SM_Q    = SM_ML + 64;
constexpr int SM_O    = SM_Q + DH * 2;
constexpr int SM_TOTAL = SM_O + 128;
constexpr int B_CONS = 1, B_Q = 2, B_O = 3, B_LATE = 4, B_L = 5, B_F = 6, B_Y = 7, B_QP = 8;
#define LATE_TILE 30

constexpr unsigned SPIN_LIMIT = 1u << 24;

struct Scratch {
    float x2[NRED * NCTA * 8];
    float x1[NCTA * SPLIT * OROWS];
    float xm[NCTA * SPLIT * 8];
    float x0[NCTA * SPLIT * DH];
    unsigned landed;
    unsigned pad[31];
    unsigned cleared;
};
__device__ __align__(128) Scratch g_scratch;

#define TL(i) do { } while (0)
#define TL_DUMP(a, b) do { } while (0)
#define TL_EXTRA 0

__device__ __forceinline__ uint32_t smem_u32(const void* p) { return (uint32_t)__cvta_generic_to_shared(p); }

__device__ __forceinline__ void mbar_init(uint32_t bar, uint32_t cnt) {
    asm volatile("mbarrier.init.shared::cta.b64 [%0], %1;" :: "r"(bar), "r"(cnt) : "memory");
}
__device__ __forceinline__ void mbar_expect_tx(uint32_t bar, uint32_t bytes) {
    asm volatile("mbarrier.arrive.expect_tx.shared::cta.b64 _, [%0], %1;" :: "r"(bar), "r"(bytes) : "memory");
}
__device__ __forceinline__ void mbar_arrive(uint32_t bar) {
    asm volatile("mbarrier.arrive.shared::cta.b64 _, [%0];" :: "r"(bar) : "memory");
}
__device__ __forceinline__ bool mbar_try(uint32_t bar, uint32_t parity) {
    uint32_t ok;
    asm volatile("{\n.reg .pred p;\nmbarrier.try_wait.parity.shared::cta.b64 p, [%1], %2;\nselp.u32 %0, 1, 0, p;\n}"
                 : "=r"(ok) : "r"(bar), "r"(parity) : "memory");
    return ok;
}
__device__ __forceinline__ bool mbar_test(uint32_t bar, uint32_t parity) {
    uint32_t ok;
    asm volatile("{\n.reg .pred p;\nmbarrier.test_wait.parity.shared::cta.b64 p, [%1], %2;\nselp.u32 %0, 1, 0, p;\n}"
                 : "=r"(ok) : "r"(bar), "r"(parity) : "memory");
    return ok;
}
__device__ __forceinline__ void mbar_spin(uint32_t bar, uint32_t parity) {
    unsigned spins = 0;
    while (!mbar_test(bar, parity)) if (++spins > SPIN_LIMIT * 16) __trap();
}
__device__ __forceinline__ void mbar_wait(uint32_t bar, uint32_t parity) {
    if (mbar_try(bar, parity)) return;
    unsigned spins = 0;
    while (!mbar_try(bar, parity)) if (++spins > SPIN_LIMIT) __trap();
}
#define EVICT_FIRST 1
__device__ __forceinline__ uint64_t stream_policy() { return 0x12F0000000000000ull; }
__device__ __forceinline__ void bulk_load(uint32_t dst, const void* src, uint32_t bytes, uint32_t bar) {
    asm volatile("cp.async.bulk.shared::cluster.global.mbarrier::complete_tx::bytes.L2::cache_hint [%0], [%1], %2, [%3], %4;"
                 :: "r"(dst), "l"(src), "r"(bytes), "r"(bar), "l"(stream_policy()) : "memory");
}
__device__ __forceinline__ void tma_2d(uint32_t dst, const CUtensorMap* tm, int c0, int c1, uint32_t bar) {
    asm volatile("cp.async.bulk.tensor.2d.shared::cluster.global.mbarrier::complete_tx::bytes.L2::cache_hint [%0], [%1, {%3, %4}], [%2], %5;"
                 :: "r"(dst), "l"(tm), "r"(bar), "r"(c0), "r"(c1), "l"(stream_policy()) : "memory");
}
__device__ __forceinline__ void tma_3d(uint32_t dst, const CUtensorMap* tm, int c0, int c1, int c2, uint32_t bar) {
    asm volatile("cp.async.bulk.tensor.3d.shared::cluster.global.mbarrier::complete_tx::bytes.L2::cache_hint [%0], [%1, {%3, %4, %5}], [%2], %6;"
                 :: "r"(dst), "l"(tm), "r"(bar), "r"(c0), "r"(c1), "r"(c2), "l"(stream_policy()) : "memory");
}
__device__ __forceinline__ void ldsm4(uint32_t (&a)[4], uint32_t addr) {
    asm volatile("ldmatrix.sync.aligned.m8n8.x4.shared.b16 {%0,%1,%2,%3}, [%4];"
                 : "=r"(a[0]), "=r"(a[1]), "=r"(a[2]), "=r"(a[3]) : "r"(addr) : "memory");
}
__device__ __forceinline__ void ldsm4t(uint32_t (&a)[4], uint32_t addr) {
    asm volatile("ldmatrix.sync.aligned.m8n8.x4.trans.shared.b16 {%0,%1,%2,%3}, [%4];"
                 : "=r"(a[0]), "=r"(a[1]), "=r"(a[2]), "=r"(a[3]) : "r"(addr) : "memory");
}
__device__ __forceinline__ void mma16816(float (&c)[4], const uint32_t (&a)[4], uint32_t b0, uint32_t b1) {
    asm volatile("mma.sync.aligned.m16n8k16.row.col.f32.bf16.bf16.f32 {%0,%1,%2,%3}, {%4,%5,%6,%7}, {%8,%9}, {%0,%1,%2,%3};"
                 : "+f"(c[0]), "+f"(c[1]), "+f"(c[2]), "+f"(c[3])
                 : "r"(a[0]), "r"(a[1]), "r"(a[2]), "r"(a[3]), "r"(b0), "r"(b1));
}
__device__ __forceinline__ void bar_sync(int id, int n) { asm volatile("bar.sync %0, %1;" :: "r"(id), "r"(n) : "memory"); }
__device__ __forceinline__ void bar_arrive(int id, int n) { asm volatile("bar.arrive %0, %1;" :: "r"(id), "r"(n) : "memory"); }

__device__ __forceinline__ uint32_t enc(float v) { uint32_t u = __float_as_uint(v); return u ? u : 0x80000000u; }
__device__ __forceinline__ void st_x(float* p, float v) {
    asm volatile("st.relaxed.gpu.global.b32 [%0], %1;" :: "l"(p), "r"(enc(v)) : "memory");
}
__device__ __forceinline__ void st_x4(float* p, float4 v) {
    asm volatile("st.relaxed.gpu.global.v4.b32 [%0], {%1,%2,%3,%4};"
                 :: "l"(p), "r"(enc(v.x)), "r"(enc(v.y)), "r"(enc(v.z)), "r"(enc(v.w)) : "memory");
}
__device__ __forceinline__ void st_x2(float* p, float a, float b) {
    asm volatile("st.relaxed.gpu.global.v2.b32 [%0], {%1,%2};" :: "l"(p), "r"(enc(a)), "r"(enc(b)) : "memory");
}
__device__ __forceinline__ void st_zero2(float* p) {
    asm volatile("st.relaxed.gpu.global.v2.b32 [%0], {%1,%1};" :: "l"(p), "r"(0) : "memory");
}
__device__ __forceinline__ void st_zero4(float* p) {
    asm volatile("st.relaxed.gpu.global.v4.b32 [%0], {%1,%1,%1,%1};" :: "l"(p), "r"(0) : "memory");
}
__device__ __forceinline__ uint4 ld_x4(const float* p) {
    uint4 v;
    asm volatile("ld.relaxed.gpu.global.v4.b32 {%0,%1,%2,%3}, [%4];" : "=r"(v.x), "=r"(v.y), "=r"(v.z), "=r"(v.w) : "l"(p) : "memory");
    return v;
}
__device__ __forceinline__ uint2 ld_x2(const float* p) {
    uint2 v;
    asm volatile("ld.relaxed.gpu.global.v2.b32 {%0,%1}, [%2];" : "=r"(v.x), "=r"(v.y) : "l"(p) : "memory");
    return v;
}
__device__ __forceinline__ uint32_t umin4(uint4 v) { return min(min(v.x, v.y), min(v.z, v.w)); }
__device__ __forceinline__ uint32_t umin2(uint2 v) { return min(v.x, v.y); }

__device__ __forceinline__ void load8(uint4 (&v)[8], const float* p) {
#pragma unroll
    for (int i = 0; i < 8; i++) v[i] = ld_x4(p + i * 128);
}
__device__ __forceinline__ uint32_t umin8(const uint4 (&v)[8]) {
    return min(min(min(umin4(v[0]), umin4(v[1])), min(umin4(v[2]), umin4(v[3]))),
               min(min(umin4(v[4]), umin4(v[5])), min(umin4(v[6]), umin4(v[7]))));
}
__device__ __forceinline__ void sum8(float (&s)[4], const uint4 (&v)[8]) {
#define GQA_SUM8(c) (((__uint_as_float(v[0].c) + __uint_as_float(v[1].c)) + (__uint_as_float(v[2].c) + __uint_as_float(v[3].c))) + \
                     ((__uint_as_float(v[4].c) + __uint_as_float(v[5].c)) + (__uint_as_float(v[6].c) + __uint_as_float(v[7].c))))
    s[0] = GQA_SUM8(x); s[1] = GQA_SUM8(y); s[2] = GQA_SUM8(z); s[3] = GQA_SUM8(w);
#undef GQA_SUM8
}
#define LAST_SPIN 0
#define QP_THROTTLE 1
#define X1_POLL2 0
#define POLL_GAP 200
#define POLL_PRED 1

__device__ __forceinline__ float bf16r(float v) { return __bfloat162float(__float2bfloat16_rn(v)); }
__device__ __forceinline__ uint32_t pack_bf16(float lo, float hi) {
    __nv_bfloat162 h = __floats2bfloat162_rn(lo, hi);
    return *reinterpret_cast<uint32_t*>(&h);
}
__device__ __forceinline__ float ex2(float v) { float r; asm("ex2.approx.ftz.f32 %0, %1;" : "=f"(r) : "f"(v)); return r; }

__device__ __forceinline__ void rowsum_group(float (&acc)[12][4], uint32_t slot, const uint32_t (&off)[4], uint32_t b0, uint32_t b1) {
#pragma unroll
    for (int s = 0; s < 3; s++) {
        uint32_t a[4][4];
#pragma unroll
        for (int j = 0; j < 4; j++) ldsm4t(a[j], slot + off[j] + s * 128);
#pragma unroll
        for (int j = 0; j < 4; j++) mma16816(acc[s * 4 + j], a[j], b0, b1);
    }
}
__device__ __forceinline__ void rowsum_finish(const float (&acc)[12][4], float* red, int lane) {
    const int g = lane >> 2, t = lane & 3;
    const int from = (lane & ~3) | ((t + 3) & 3);
#pragma unroll
    for (int s = 0; s < 3; s++) {
        float val[8];
#pragma unroll
        for (int j = 0; j < 4; j++) {
            val[2 * j]     = acc[s * 4 + j][0] + acc[s * 4 + ((j + 3) & 3)][3];
            val[2 * j + 1] = acc[s * 4 + j][1] + acc[s * 4 + j][2];
        }
        float nw[4];
#pragma unroll
        for (int v = 0; v < 4; v++) nw[v] = val[v] + __shfl_xor_sync(0xffffffffu, val[v + 4], 2);
#pragma unroll
        for (int v = 0; v < 2; v++) {
            float f = nw[v] + __shfl_sync(0xffffffffu, nw[v + 2], from);
            red[64 * s + 8 * (2 * t + v) + g] = f;
        }
    }
}

__device__ __forceinline__ void issue_wq(uint32_t ring, uint32_t full, const CUtensorMap* tm, int h, int r, int i) {
    mbar_expect_tx(full + 8 * i, i < 2 ? SLOT : SLOT / 2);
    tma_2d(ring + i * SLOT, tm, h * DH, r * XROWS + i * 64, full + 8 * i);
    if (i < 2) tma_2d(ring + i * SLOT + SLOT / 2, tm, h * DH, r * XROWS + i * 64 + 32, full + 8 * i);
}

__global__ void __launch_bounds__(NTHREADS, 1)
gqa_decode_kernel(const __nv_bfloat16* __restrict__ kc, const __nv_bfloat16* __restrict__ vc,
                  const __nv_bfloat16* __restrict__ x, __nv_bfloat16* __restrict__ out, Scratch* __restrict__ sc,
                  const __grid_constant__ CUtensorMap tm_wq, const __grid_constant__ CUtensorMap tm_wo) {
    extern __shared__ __align__(1024) unsigned char smem[];
    const int tid = threadIdx.x, warp = tid >> 5, lane = tid & 31;
    const int cta = blockIdx.x, h = cta >> 2, r = cta & 3;
    const uint32_t ring = smem_u32(smem) + SM_RING;
    const uint32_t full = smem_u32(smem) + SM_BARS, empty = full + NSLOT * 8;
    const unsigned char* kp = reinterpret_cast<const unsigned char*>(kc) + (size_t)cta * (TOK_CTA * ROWB);

    TL(0);
    if (tid == 0) {
        TL(30);
        mbar_init(full + 8 * IT_K, 1);
        asm volatile("fence.mbarrier_init.release.cluster;" ::: "memory");
        mbar_expect_tx(full + 8 * IT_K, SLOT);
        bulk_load(ring + IT_K * SLOT, kp, SLOT, full + 8 * IT_K);
        TL(28);
#pragma unroll
        for (int i = 0; i < NSLOT; i++) if (i != IT_K) mbar_init(full + 8 * i, 1);
        asm volatile("fence.mbarrier_init.release.cluster;" ::: "memory");
#pragma unroll
        for (int i = 0; i < WIN_HEAD - 1 && i < 3; i++) issue_wq(ring, full, &tm_wq, h, r, i);
        TL(29);
#pragma unroll
        for (int i = 0; i < NSLOT; i++) mbar_init(empty + 8 * i, NCW + 1);
        TL(15);
    }
    __syncthreads();
    const float LOG2E = 1.4426950408889634f;
    const int g = lane >> 2, t = lane & 3;
    float* ml = reinterpret_cast<float*>(smem + SM_ML);

    if (warp == 0) {
        if (lane == 0) {
            const unsigned char* vp = reinterpret_cast<const unsigned char*>(vc) + (size_t)cta * (TOK_CTA * ROWB);
            asm volatile("prefetch.tensormap [%0];" :: "l"(&tm_wo) : "memory");
#pragma unroll
            for (int i = WIN_HEAD - 1; i < 3; i++) {
                mbar_wait(full + 8 * (i + 1 - WIN_HEAD == 0 ? IT_K : i - WIN_HEAD), 0);
                issue_wq(ring, full, &tm_wq, h, r, i);
            }
            int landed = 0;
            TL(19);
#pragma unroll 1
            for (int it = IT_K + 1; it < IT_END; it++) {
                const int s = it & (NSLOT - 1);
                const int win = it < HEAD_UNTIL ? WIN_HEAD : WIN_MID;
                if (it - IT_K >= PACE_FROM) {
                    const int need = it < IT_O ? NCTA * (it - IT_K) + PACE_STAG * cta - PACE_DELTA
                                               : min(NCTA * 2 * NTILE - (it == IT_O ? PACE_D0 : it == IT_O + 1 ? PACE_D1 : PACE_D2) + ((cta * PACE_SO) >> 2),
                                                     NCTA * 2 * NTILE - PACE_CLAMP);
                    unsigned spins = 0;
                    while (landed < need) {
                        asm volatile("ld.relaxed.gpu.global.b32 %0, [%1];" : "=r"(landed) : "l"(&sc->landed) : "memory");
                        if (++spins > SPIN_LIMIT) __trap();
                    }
                }
                if (win < NSLOT) {
                    int j = it - win;
                    if (j <= IT_K) j = j <= 0 ? IT_K : j - 1;
                    mbar_wait(full + 8 * (j & (NSLOT - 1)), (j / NSLOT) & 1);
                }
                if (it >= NSLOT) mbar_wait(empty + 8 * s, ((it / NSLOT) & 1) ^ 1);
                if (it < IT_O) {
                    mbar_expect_tx(full + 8 * s, SLOT);
                    bulk_load(ring + s * SLOT, it < IT_V ? kp + (size_t)(it - IT_K) * SLOT : vp + (size_t)(it - IT_V) * SLOT, SLOT, full + 8 * s);
                    if (it < 12) TL(16 + it);
                } else {
                    mbar_expect_tx(full + 8 * s, WOB);
                    tma_3d(ring + s * SLOT, &tm_wo, 0, cta * OROWS + (it - IT_O) * 16, 0, full + 8 * s);
                    TL(16 + it - IT_O);
                }
            }
        }
        return;
    }

    if (warp == W_COUNT) {
        if (lane == 0) {
            mbar_arrive(empty);
            mbar_arrive(empty + 8);
            mbar_arrive(empty + 16);
        }
#pragma unroll 1
        for (int it = IT_K; it < IT_O; it++) {
            const int s = it & (NSLOT - 1);
            mbar_wait(full + 8 * s, (it / NSLOT) & 1);
            TL(32 + it);
            if (lane == 0) {
                asm volatile("red.relaxed.gpu.global.add.u32 [%0], 1;" :: "l"(&sc->landed) : "memory");
                mbar_arrive(empty + 8 * s);
            }
            if (it == IT_V + LATE_TILE) bar_arrive(B_LATE, 64);
        }
        return;
    }

    if (warp == W_XCHG) {
        {
            float* in = sc->x0 + cta * SPLIT * DH + 2 * lane;
            uint2 v[SPLIT][3];
            unsigned spins = 0, lo;
            do {
#pragma unroll
                for (int s = 0; s < SPLIT; s++)
#pragma unroll
                    for (int i = 0; i < 3; i++) v[s][i] = ld_x2(in + s * DH + i * 64);
                lo = 0xffffffffu;
#pragma unroll
                for (int s = 0; s < SPLIT; s++)
#pragma unroll
                    for (int i = 0; i < 3; i++) lo = min(lo, umin2(v[s][i]));
                if (spins == 0) bar_sync(B_QP, (NCW + 1) * 32);
                if (++spins > SPIN_LIMIT) __trap();
            } while (lo == 0);
            uint32_t* qw = reinterpret_cast<uint32_t*>(smem + SM_Q);
#pragma unroll
            for (int i = 0; i < 3; i++) {
                float a = (__uint_as_float(v[0][i].x) + __uint_as_float(v[1][i].x)) + (__uint_as_float(v[2][i].x) + __uint_as_float(v[3][i].x));
                float b = (__uint_as_float(v[0][i].y) + __uint_as_float(v[1][i].y)) + (__uint_as_float(v[2][i].y) + __uint_as_float(v[3][i].y));
                qw[i * 32 + lane] = pack_bf16(a, b);
            }
            bar_arrive(B_Q, (NCW + 1) * 32);
#pragma unroll
            for (int s = 0; s < SPLIT; s++)
#pragma unroll
                for (int i = 0; i < 3; i++) st_zero2(in + s * DH + i * 64);
        }
        {
            unsigned cleared, spins0 = 0;
            do {
                asm volatile("ld.relaxed.gpu.global.b32 %0, [%1];" : "=r"(cleared) : "l"(&sc->cleared) : "memory");
                if (++spins0 > SPIN_LIMIT) __trap();
            } while (cleared < NCTA);
            asm volatile("fence.acq_rel.gpu;" ::: "memory");
            bar_sync(B_L, (NCW + 1) * 32);
            const float m = fmaxf(fmaxf(ml[0], ml[1]), fmaxf(ml[2], ml[3]));
            const float l = (ml[4] + ml[5]) + (ml[6] + ml[7]);
            if (lane < 2 * SPLIT) st_x4(sc->xm + ((h * SPLIT + (lane >> 1)) * SPLIT + r) * 8 + (lane & 1) * 4, make_float4(m, l, m, l));
            float* in = sc->xm + (cta * SPLIT + (lane & 3)) * 8;
            uint2 v;
            unsigned spins = 0;
            do {
                v = ld_x2(in);
                if (++spins > SPIN_LIMIT) __trap();
            } while (umin2(v) == 0);
            __syncwarp();
            const float ms = __uint_as_float(v.x);
            float mm = fmaxf(ms, __shfl_xor_sync(0xffffffffu, ms, 1));
            mm = fmaxf(mm, __shfl_xor_sync(0xffffffffu, mm, 2));
            float ll = __uint_as_float(v.y) * ex2((ms - mm) * LOG2E);
            ll += __shfl_xor_sync(0xffffffffu, ll, 1);
            ll += __shfl_xor_sync(0xffffffffu, ll, 2);
            if (lane == 0) ml[8] = ex2((m - mm) * LOG2E) / ll;
            bar_arrive(B_F, (NCW + 1) * 32);
        }
        {
            bar_sync(B_LATE, 64);
            const int j = lane < 24 ? lane : 0;
            float* in = sc->x1 + cta * SPLIT * OROWS + 2 * j;
            float a, b;
            unsigned spins = 0;
            auto ld4 = [&](uint2 (&v)[SPLIT]) {
#pragma unroll
                for (int s = 0; s < SPLIT; s++) v[s] = ld_x2(in + s * OROWS);
            };
            auto done = [&](const uint2 (&v)[SPLIT]) {
                if (min(min(umin2(v[0]), umin2(v[1])), min(umin2(v[2]), umin2(v[3]))) == 0) return false;
                a = (__uint_as_float(v[0].x) + __uint_as_float(v[1].x)) + (__uint_as_float(v[2].x) + __uint_as_float(v[3].x));
                b = (__uint_as_float(v[0].y) + __uint_as_float(v[1].y)) + (__uint_as_float(v[2].y) + __uint_as_float(v[3].y));
                return true;
            };
            uint2 v[SPLIT];
            do {
                ld4(v);
                if (++spins > SPIN_LIMIT) __trap();
            } while (!done(v));
            if (lane < 24) reinterpret_cast<uint32_t*>(smem + SM_O)[(j >> 3) * 8 + (j & 3) * 2 + ((j >> 2) & 1)] = pack_bf16(a, b);
            bar_arrive(B_O, (NCW + 1) * 32);
            TL(14);
            TL_DUMP(14, 16);
        }
        return;
    }

    if (warp >= W_RED) {
        float* p = sc->x2 + cta * NCTA * 8 + lane * 4;
        volatile uint32_t* flag = reinterpret_cast<volatile uint32_t*>(ml + 9);
        if (warp == W_RED) {
        if (lane == 0) *flag = 0;
        st_zero4(sc->x1 + cta * SPLIT * OROWS + lane * 4);
        if (lane < 16) st_zero4(sc->x1 + cta * SPLIT * OROWS + 128 + lane * 4);
        if (lane < 2 * SPLIT) st_zero4(sc->xm + cta * SPLIT * 8 + lane * 4);
        if (cta < NRED) {
#pragma unroll
            for (int i = 0; i < 8; i++) st_zero4(p + i * 128);
        }
        __syncwarp();
        if (lane == 0) {
            asm volatile("fence.acq_rel.gpu;" ::: "memory");
            asm volatile("red.relaxed.gpu.global.add.u32 [%0], 1;" :: "l"(&sc->cleared) : "memory");
        }
        }
        if (cta >= NRED) return;
        __nv_bfloat16* po = out + cta * 8 + (lane & 1) * 4 + (lane >> 3);
        asm volatile("" : "+l"(p), "+l"(po));
        bar_sync(B_Y, (NCW + NREDW) * 32);
        float s[4];
        {
            uint4 v[8];
            unsigned spins = 0;
            if (NREDW > 1 && warp > W_RED) {
                const unsigned c0 = clock();
                while (clock() - c0 < (warp - W_RED) * POLL_GAP) { }
            }
            load8(v, p);
            for (;;) {
                if (__all_sync(0xffffffffu, umin8(v) != 0)) break;
                if (NREDW > 1 && *flag) return;
#pragma unroll
                for (int i = 0; i < 8; i++) if (!POLL_PRED || umin4(v[i]) == 0) v[i] = ld_x4(p + i * 128);
                if (++spins > SPIN_LIMIT) __trap();
            }
            if (NREDW > 1) *flag = 1;
            sum8(s, v);
        }
        __syncwarp();
        TL(12);
        const bool up = lane & 16;
        float a0 = (up ? s[2] : s[0]) + __shfl_xor_sync(0xffffffffu, up ? s[0] : s[2], 16);
        float a1 = (up ? s[3] : s[1]) + __shfl_xor_sync(0xffffffffu, up ? s[1] : s[3], 16);
        const bool up2 = lane & 8;
        float b = (up2 ? a1 : a0) + __shfl_xor_sync(0xffffffffu, up2 ? a0 : a1, 8);
        b += __shfl_xor_sync(0xffffffffu, b, 4);
        b += __shfl_xor_sync(0xffffffffu, b, 2);
        if ((lane & 6) == 0) *po = __float2bfloat16_rn(b);
        TL(13);
        if (cta == 0 && lane < 2) asm volatile("st.relaxed.gpu.global.b32 [%0], %1;" :: "l"(&sc->landed + 32 * lane), "r"(0) : "memory");
        TL_DUMP(12, 14);
        return;
    }

    const int cw = warp - 1;
    const bool diag = (t == (g >> 1));
    const uint32_t sel0 = diag ? ((g & 1) ? 0x1044u : 0x4410u) : 0x4444u;
    const uint32_t sel1 = diag ? ((g & 1) ? 0x3244u : 0x4432u) : 0x4444u;
    uint32_t offk[4], offv[4];
    {
        const int mi = lane >> 3, rr = lane & 7;
#pragma unroll
        for (int j = 0; j < 4; j++) {
            offk[j] = cw * GRP + (rr + 8 * (mi & 1)) * ROWB + ((2 * j + (mi >> 1) + rr) & 7) * 16;
            offv[j] = cw * GRP + (rr + 8 * (mi >> 1)) * ROWB + ((2 * j + (mi & 1) + rr) & 7) * 16;
        }
    }
    float* red = reinterpret_cast<float*>(smem + SM_RED);
    uint32_t* pw = reinterpret_cast<uint32_t*>(smem + SM_P) + cw * (NTILE * 8);
    auto release = [&](int s) { __syncwarp(); if (lane == 0) mbar_arrive(empty + 8 * s); };

    float acc[12][4];
    {
        const int nq = cw < 2 ? 3 : 2;
        uint32_t xw[3];
#pragma unroll
        for (int i = 0; i < 3; i++) {
            xw[i] = 0;
            if (i < nq) {
                const unsigned short* xs = reinterpret_cast<const unsigned short*>(x) + r * XROWS + (cw + 4 * i) * 16 + g;
                xw[i] = (uint32_t)__ldg(xs) | ((uint32_t)__ldg(xs + 8) << 16);
            }
        }
#pragma unroll
        for (int i = 0; i < 12; i++) { acc[i][0] = acc[i][1] = acc[i][2] = acc[i][3] = 0.f; }
#pragma unroll 1
        for (int i = 0; i < 3; i++) {
            mbar_wait(full + 8 * i, 0);
            if (i == 2) TL(1);
            const uint32_t w = i == 0 ? xw[0] : (i == 1 ? xw[1] : xw[2]);
            if (i < nq) rowsum_group(acc, ring + i * SLOT, offv, __byte_perm(w, 0, sel0), __byte_perm(w, 0, sel1));
            release(i);
        }
        TL(2);
        rowsum_finish(acc, red + cw * DH, lane);
        bar_sync(B_CONS, NCW * 32);
        const float2* r2 = reinterpret_cast<const float2*>(red);
        float* dst = sc->x0 + ((h * SPLIT + cw) * SPLIT + r) * DH + 2 * lane;
#pragma unroll
        for (int i = 0; i < 3; i++) {
            const float2 a = r2[i * 32 + lane], b = r2[DH / 2 + i * 32 + lane], c = r2[DH + i * 32 + lane], d = r2[3 * DH / 2 + i * 32 + lane];
            st_x2(dst + i * 64, (a.x + b.x) + (c.x + d.x), (a.y + b.y) + (c.y + d.y));
        }
        bar_arrive(B_QP, (NCW + 1) * 32);
        bar_sync(B_Q, (NCW + 1) * 32);
    }

    float mx = -INFINITY;
    {
        const uint32_t* qw = reinterpret_cast<const uint32_t*>(smem + SM_Q);
        uint32_t qb[3][8];
#pragma unroll
        for (int s = 0; s < 3; s++)
#pragma unroll
            for (int u = 0; u < 8; u++) qb[s][u] = qw[32 * s + 4 * ((u + g) & 7) + t];
        TL(3);
        const float scale = 0.07216878364870322f;
#pragma unroll 1
        for (int i = 0; i < NTILE; i++) {
            const int it = IT_K + i, slot = it & (NSLOT - 1);
            mbar_wait(full + 8 * slot, (it / NSLOT) & 1);
            const uint32_t sa = ring + slot * SLOT;
            float c[3][4];
#pragma unroll
            for (int s = 0; s < 3; s++) {
                uint32_t a[4][4];
                c[s][0] = c[s][1] = c[s][2] = c[s][3] = 0.f;
#pragma unroll
                for (int j = 0; j < 4; j++) ldsm4(a[j], sa + offk[j] + s * 128);
#pragma unroll
                for (int j = 0; j < 4; j++) mma16816(c[s], a[j], qb[s][2 * j], qb[s][2 * j + 1]);
            }
            release(slot);
            const bool odd = g & 1;
            float lo = odd ? (c[0][1] + c[1][1]) + c[2][1] : (c[0][0] + c[1][0]) + c[2][0];
            float hi = odd ? (c[0][3] + c[1][3]) + c[2][3] : (c[0][2] + c[1][2]) + c[2][2];
            lo = bf16r(bf16r(lo) * scale);
            hi = bf16r(bf16r(hi) * scale);
            if (diag) {
                mx = fmaxf(mx, fmaxf(lo, hi));
                pw[i * 8 + g] = pack_bf16(lo, hi);
            }
        }
    }
    TL(4);
    {
#pragma unroll
        for (int o = 16; o > 0; o >>= 1) mx = fmaxf(mx, __shfl_xor_sync(0xffffffffu, mx, o));
        if (lane == 0) ml[cw] = mx;
        bar_sync(B_CONS, NCW * 32);
        mx = fmaxf(fmaxf(ml[0], ml[1]), fmaxf(ml[2], ml[3]));
        float lsum = 0.f;
#pragma unroll
        for (int i = 0; i < NTILE * 8 / 32; i++) {
            uint32_t w = pw[i * 32 + lane];
            float e0 = ex2((__uint_as_float(w << 16) - mx) * LOG2E);
            float e1 = ex2((__uint_as_float(w & 0xffff0000u) - mx) * LOG2E);
            lsum += e0 + e1;
            pw[i * 32 + lane] = pack_bf16(e0, e1);
        }
#pragma unroll
        for (int o = 16; o > 0; o >>= 1) lsum += __shfl_xor_sync(0xffffffffu, lsum, o);
        if (lane == 0) ml[4 + cw] = lsum;
        __syncwarp();
        bar_arrive(B_L, (NCW + 1) * 32);
    }
    TL(5);
#pragma unroll
    for (int i = 0; i < 12; i++) { acc[i][0] = acc[i][1] = acc[i][2] = acc[i][3] = 0.f; }
#pragma unroll 1
    for (int i = 0; i < NTILE; i++) {
        const int it = IT_V + i, slot = it & (NSLOT - 1);
        const uint32_t w = pw[i * 8 + g];
        mbar_wait(full + 8 * slot, (it / NSLOT) & 1);
        rowsum_group(acc, ring + slot * SLOT, offv, __byte_perm(w, 0, sel0), __byte_perm(w, 0, sel1));
        release(slot);
    }
    TL(6);
    rowsum_finish(acc, red + cw * DH, lane);
    bar_sync(B_F, (NCW + 1) * 32);
    if (lane < 12) {
        const float f = ml[8];
        const float4* r4 = reinterpret_cast<const float4*>(red) + cw * 12 + lane;
        const float4 a = r4[0], b = r4[DH / 4], c = r4[2 * DH / 4], d = r4[3 * DH / 4];
        st_x4(sc->x1 + ((h * SPLIT + cw) * SPLIT + r) * OROWS + lane * 4,
              make_float4(((a.x + b.x) + (c.x + d.x)) * f, ((a.y + b.y) + (c.y + d.y)) * f,
                          ((a.z + b.z) + (c.z + d.z)) * f, ((a.w + b.w) + (c.w + d.w)) * f));
    }
    __syncwarp();
    TL(7);
    {
        uint32_t offw = ring + ((lane & 7) + 8 * (lane >> 4)) * 128 + (((2 * cw + ((lane >> 3) & 1)) ^ (lane & 7)) * 16);
        float* dst = sc->x2 + ((8 * (t >> 1) + 2 * cw + (t & 1)) * NCTA + cta) * 8 + g;
        asm volatile("" : "+r"(offw), "+l"(dst));
        constexpr int S0 = IT_O & (NSLOT - 1), S1 = (IT_O + 1) & (NSLOT - 1), S2 = (IT_O + 2) & (NSLOT - 1);
        constexpr int P0 = (IT_O / NSLOT) & 1, P1 = ((IT_O + 1) / NSLOT) & 1, P2 = ((IT_O + 2) / NSLOT) & 1;
        uint32_t a0[10][4], a1[10][4], a2[10][4];
        mbar_wait(full + 8 * S0, P0);
#pragma unroll
        for (int b = 0; b < 10; b++) ldsm4t(a0[b], offw + b * 2048 + S0 * SLOT);
        mbar_wait(full + 8 * S1, P1);
#pragma unroll
        for (int b = 0; b < 10; b++) ldsm4t(a1[b], offw + b * 2048 + S1 * SLOT);
        bar_sync(B_O, (NCW + 1) * 32);
        uint2 ob[3];
#pragma unroll
        for (int ks = 0; ks < 3; ks++) ob[ks] = reinterpret_cast<const uint2*>(smem + SM_O)[ks * 4 + t];
        const bool early = __all_sync(0xffffffffu, mbar_test(full + 8 * S2, P2));
        TL(8);
        float y[10][4];
#pragma unroll
        for (int b = 0; b < 10; b++) { y[b][0] = y[b][1] = y[b][2] = y[b][3] = 0.f; }
        if (early) {
#pragma unroll
            for (int b = 0; b < 10; b++) ldsm4t(a2[b], offw + b * 2048 + S2 * SLOT);
        }
#pragma unroll
        for (int b = 0; b < 10; b++) mma16816(y[b], a0[b], ob[0].x, ob[0].y);
#pragma unroll
        for (int b = 0; b < 10; b++) mma16816(y[b], a1[b], ob[1].x, ob[1].y);
        if (!early) {
            mbar_wait(full + 8 * S2, P2);
#pragma unroll
            for (int b = 0; b < 10; b++) ldsm4t(a2[b], offw + b * 2048 + S2 * SLOT);
        }
        TL(9);
#pragma unroll
        for (int b = 0; b < 10; b++) mma16816(y[b], a2[b], ob[2].x, ob[2].y);
#pragma unroll
        for (int i = 0; i < 5; i++) {
            const float v = (t & 2) ? ((t & 1) ? y[2 * i + 1][2] : y[2 * i + 1][0]) : ((t & 1) ? y[2 * i][2] : y[2 * i][0]);
            st_x(dst + i * 16 * NCTA * 8, v);
        }
        if (cta < NRED) bar_arrive(B_Y, (NCW + NREDW) * 32);
        TL(10);
        if (warp == 1) TL_DUMP(0, 12);
    }
}

typedef CUresult (*EncodeTiledFn)(CUtensorMap*, CUtensorMapDataType, cuuint32_t, void*, const cuuint64_t*, const cuuint64_t*,
                                  const cuuint32_t*, const cuuint32_t*, CUtensorMapInterleave, CUtensorMapSwizzle,
                                  CUtensorMapL2promotion, CUtensorMapFloatOOBfill);

}

extern "C" void kernel_launch(void* const* d_in, const int* in_sizes, int n_in, void* d_out, int out_size) {
    (void)in_sizes; (void)n_in; (void)out_size;
    using namespace gqa;
    static EncodeTiledFn encode = nullptr;
    static Scratch* scratch = nullptr;
    if (!encode) {
        cudaGetSymbolAddress((void**)&scratch, g_scratch);
        void* fn = nullptr;
        cudaDriverEntryPointQueryResult qr;
        cudaGetDriverEntryPoint("cuTensorMapEncodeTiled", &fn, cudaEnableDefault, &qr);
        encode = (EncodeTiledFn)fn;
        cudaFuncSetAttribute(gqa_decode_kernel, cudaFuncAttributeMaxDynamicSharedMemorySize, SM_TOTAL + TL_EXTRA);
    }
    CUtensorMap tm_wq, tm_wo;
    {
        cuuint64_t dims[2] = {QCOLS, D_MODEL}, strides[1] = {QCOLS * 2};
        cuuint32_t box[2] = {DH, 32}, es[2] = {1, 1};
        encode(&tm_wq, CU_TENSOR_MAP_DATA_TYPE_BFLOAT16, 2, d_in[3], dims, strides, box, es, CU_TENSOR_MAP_INTERLEAVE_NONE,
               CU_TENSOR_MAP_SWIZZLE_NONE, CU_TENSOR_MAP_L2_PROMOTION_NONE, CU_TENSOR_MAP_FLOAT_OOB_FILL_NONE);
    }
    {
        cuuint64_t dims[3] = {64, QCOLS, D_MODEL / 64}, strides[2] = {D_MODEL * 2, 128};
        cuuint32_t box[3] = {64, 16, D_MODEL / 64}, es[3] = {1, 1, 1};
        encode(&tm_wo, CU_TENSOR_MAP_DATA_TYPE_BFLOAT16, 3, d_in[4], dims, strides, box, es, CU_TENSOR_MAP_INTERLEAVE_NONE,
               CU_TENSOR_MAP_SWIZZLE_128B, CU_TENSOR_MAP_L2_PROMOTION_NONE, CU_TENSOR_MAP_FLOAT_OOB_FILL_NONE);
    }
    gqa_decode_kernel<<<NCTA, NTHREADS, SM_TOTAL + TL_EXTRA>>>((const __nv_bfloat16*)d_in[1], (const __nv_bfloat16*)d_in[2],
                                                    (const __nv_bfloat16*)d_in[0], (__nv_bfloat16*)d_out, scratch, tm_wq, tm_wo);
}
```

```cpp
#include <cuda_runtime.h>
#include <cuda.h>
#include <cuda_bf16.h>
#include <stdint.h>

namespace gqa {

constexpr int D_MODEL = 640;
constexpr int NH      = 32;
constexpr int SK      = 8192;
constexpr int DH      = 192;
constexpr int QCOLS   = NH * DH;
constexpr int SPLIT   = 4;
constexpr int NCTA    = NH * SPLIT;
constexpr int NCW     = 4;
constexpr int W_XCHG = NCW + 1, W_COUNT = NCW + 2, W_RED = NCW + 3;
constexpr int NTHREADS = (NCW + 4) * 32;
constexpr int TOK_CTA = SK / SPLIT;
constexpr int NTILE   = TOK_CTA / 64;
constexpr int ROWB    = DH * 2;
constexpr int GRP     = 16 * ROWB;
constexpr int SLOT    = NCW * GRP;
constexpr int NSLOT   = 8;
constexpr int XROWS   = D_MODEL / SPLIT;
constexpr int OROWS   = DH / SPLIT;
constexpr int WOB     = 16 * D_MODEL * 2;
constexpr int NRED    = D_MODEL / 8;
constexpr int IT_K = 3, IT_V = IT_K + NTILE, IT_O = IT_V + NTILE, IT_END = IT_O + 3;

constexpr int WIN_HEAD = 3, HEAD_UNTIL = NSLOT + IT_K;
constexpr int PACE_FROM = 48, PACE_KV = 640, PACE_WO = 384, PACE_MIN = 32;

constexpr int SM_RING = 0;
constexpr int SM_BARS = SM_RING + NSLOT * SLOT;
constexpr int SM_P    = SM_BARS + 128;
constexpr int SM_RED  = SM_P + NCW * NTILE * 8 * 4;
constexpr int SM_ML   = SM_RED + NCW * DH * 4;
constexpr int SM_Q    = SM_ML + 64;
constexpr int SM_O    = SM_Q + DH * 2;
constexpr int SM_TOTAL = SM_O + 128;
constexpr int B_CONS = 1, B_Q = 2, B_L = 3, B_F = 4, B_LATE = 5, B_O = 6, B_Y = 7;
constexpr int N_CX = (NCW + 1) * 32;

constexpr unsigned MBAR_LIMIT = 1u << 19, POLL_LIMIT = 1u << 22;

struct Scratch {
    float x2[NRED * NCTA * 8];
    float x0[NCTA * SPLIT * DH];
    float x1[NCTA * SPLIT * OROWS];
    float xm[NCTA * SPLIT * 8];
    unsigned landed;
    unsigned pad[31];
    unsigned cleared;
};
__device__ __align__(128) Scratch g_scratch;

__device__ __forceinline__ uint32_t smem_u32(const void* p) { return (uint32_t)__cvta_generic_to_shared(p); }

__device__ __forceinline__ void mbar_init(uint32_t bar, uint32_t cnt) {
    asm volatile("mbarrier.init.shared::cta.b64 [%0], %1;" :: "r"(bar), "r"(cnt) : "memory");
}
__device__ __forceinline__ void mbar_init_fence() { asm volatile("fence.mbarrier_init.release.cluster;" ::: "memory"); }
__device__ __forceinline__ void mbar_expect_tx(uint32_t bar, uint32_t bytes) {
    asm volatile("mbarrier.arrive.expect_tx.shared::cta.b64 _, [%0], %1;" :: "r"(bar), "r"(bytes) : "memory");
}
__device__ __forceinline__ void mbar_arrive(uint32_t bar) {
    asm volatile("mbarrier.arrive.shared::cta.b64 _, [%0];" :: "r"(bar) : "memory");
}
__device__ __forceinline__ bool mbar_try(uint32_t bar, uint32_t parity) {
    uint32_t ok;
    asm volatile("{\n.reg .pred p;\nmbarrier.try_wait.parity.shared::cta.b64 p, [%1], %2;\nselp.u32 %0, 1, 0, p;\n}"
                 : "=r"(ok) : "r"(bar), "r"(parity) : "memory");
    return ok;
}
__device__ __forceinline__ bool mbar_test(uint32_t bar, uint32_t parity) {
    uint32_t ok;
    asm volatile("{\n.reg .pred p;\nmbarrier.test_wait.parity.shared::cta.b64 p, [%1], %2;\nselp.u32 %0, 1, 0, p;\n}"
                 : "=r"(ok) : "r"(bar), "r"(parity) : "memory");
    return ok;
}
__device__ __forceinline__ void mbar_wait(uint32_t bar, uint32_t parity) {
    if (mbar_try(bar, parity)) return;
    unsigned spins = 0;
    while (!mbar_try(bar, parity)) if (++spins > MBAR_LIMIT) __trap();
}
__device__ __forceinline__ void wait_item(uint32_t full, unsigned it) { mbar_wait(full + 8 * (it % NSLOT), (it / NSLOT) & 1); }

constexpr uint64_t STREAM = 0x12F0000000000000ull;
__device__ __forceinline__ void bulk_load(uint32_t dst, const void* src, uint32_t bytes, uint32_t bar) {
    asm volatile("cp.async.bulk.shared::cluster.global.mbarrier::complete_tx::bytes.L2::cache_hint [%0], [%1], %2, [%3], %4;"
                 :: "r"(dst), "l"(src), "r"(bytes), "r"(bar), "l"(STREAM) : "memory");
}
__device__ __forceinline__ void tma_2d(uint32_t dst, const CUtensorMap* tm, int c0, int c1, uint32_t bar) {
    asm volatile("cp.async.bulk.tensor.2d.shared::cluster.global.mbarrier::complete_tx::bytes.L2::cache_hint [%0], [%1, {%3, %4}], [%2], %5;"
                 :: "r"(dst), "l"(tm), "r"(bar), "r"(c0), "r"(c1), "l"(STREAM) : "memory");
}
__device__ __forceinline__ void tma_3d(uint32_t dst, const CUtensorMap* tm, int c0, int c1, int c2, uint32_t bar) {
    asm volatile("cp.async.bulk.tensor.3d.shared::cluster.global.mbarrier::complete_tx::bytes.L2::cache_hint [%0], [%1, {%3, %4, %5}], [%2], %6;"
                 :: "r"(dst), "l"(tm), "r"(bar), "r"(c0), "r"(c1), "r"(c2), "l"(STREAM) : "memory");
}
__device__ __forceinline__ void ldsm4(uint32_t (&a)[4], uint32_t addr) {
    asm volatile("ldmatrix.sync.aligned.m8n8.x4.shared.b16 {%0,%1,%2,%3}, [%4];"
                 : "=r"(a[0]), "=r"(a[1]), "=r"(a[2]), "=r"(a[3]) : "r"(addr) : "memory");
}
__device__ __forceinline__ void ldsm4t(uint32_t (&a)[4], uint32_t addr) {
    asm volatile("ldmatrix.sync.aligned.m8n8.x4.trans.shared.b16 {%0,%1,%2,%3}, [%4];"
                 : "=r"(a[0]), "=r"(a[1]), "=r"(a[2]), "=r"(a[3]) : "r"(addr) : "memory");
}
__device__ __forceinline__ void mma16816(float (&c)[4], const uint32_t (&a)[4], uint32_t b0, uint32_t b1) {
    asm volatile("mma.sync.aligned.m16n8k16.row.col.f32.bf16.bf16.f32 {%0,%1,%2,%3}, {%4,%5,%6,%7}, {%8,%9}, {%0,%1,%2,%3};"
                 : "+f"(c[0]), "+f"(c[1]), "+f"(c[2]), "+f"(c[3])
                 : "r"(a[0]), "r"(a[1]), "r"(a[2]), "r"(a[3]), "r"(b0), "r"(b1));
}
__device__ __forceinline__ void bar_sync(int id, int n) { asm volatile("bar.sync %0, %1;" :: "r"(id), "r"(n) : "memory"); }
__device__ __forceinline__ void bar_arrive(int id, int n) { asm volatile("bar.arrive %0, %1;" :: "r"(id), "r"(n) : "memory"); }
__device__ __forceinline__ void fence_gpu() { asm volatile("fence.acq_rel.gpu;" ::: "memory"); }

__device__ __forceinline__ uint32_t enc(float v) { uint32_t u = __float_as_uint(v); return u ? u : 0x80000000u; }
__device__ __forceinline__ void st_x(float* p, float v) {
    asm volatile("st.relaxed.gpu.global.b32 [%0], %1;" :: "l"(p), "r"(enc(v)) : "memory");
}
__device__ __forceinline__ void st_x2(float* p, float a, float b) {
    asm volatile("st.relaxed.gpu.global.v2.b32 [%0], {%1,%2};" :: "l"(p), "r"(enc(a)), "r"(enc(b)) : "memory");
}
__device__ __forceinline__ void st_x4(float* p, float4 v) {
    asm volatile("st.relaxed.gpu.global.v4.b32 [%0], {%1,%2,%3,%4};"
                 :: "l"(p), "r"(enc(v.x)), "r"(enc(v.y)), "r"(enc(v.z)), "r"(enc(v.w)) : "memory");
}
__device__ __forceinline__ void st_zero4(float* p) {
    asm volatile("st.relaxed.gpu.global.v4.b32 [%0], {%1,%1,%1,%1};" :: "l"(p), "r"(0) : "memory");
}
__device__ __forceinline__ uint32_t ld_x(const unsigned* p) {
    uint32_t v;
    asm volatile("ld.relaxed.gpu.global.b32 %0, [%1];" : "=r"(v) : "l"(p) : "memory");
    return v;
}
__device__ __forceinline__ uint2 ld_x2(const float* p) {
    uint2 v;
    asm volatile("ld.relaxed.gpu.global.v2.b32 {%0,%1}, [%2];" : "=r"(v.x), "=r"(v.y) : "l"(p) : "memory");
    return v;
}
__device__ __forceinline__ uint4 ld_x4(const float* p) {
    uint4 v;
    asm volatile("ld.relaxed.gpu.global.v4.b32 {%0,%1,%2,%3}, [%4];" : "=r"(v.x), "=r"(v.y), "=r"(v.z), "=r"(v.w) : "l"(p) : "memory");
    return v;
}
__device__ __forceinline__ void count(unsigned* p) { asm volatile("red.relaxed.gpu.global.add.u32 [%0], 1;" :: "l"(p) : "memory"); }
__device__ __forceinline__ uint32_t umin2(uint2 v) { return min(v.x, v.y); }
__device__ __forceinline__ uint32_t umin4(uint4 v) { return min(min(v.x, v.y), min(v.z, v.w)); }
__device__ __forceinline__ float f32(uint32_t u) { return __uint_as_float(u); }
__device__ __forceinline__ float sum4(float a, float b, float c, float d) { return (a + b) + (c + d); }

__device__ __forceinline__ float bf16r(float v) { return __bfloat162float(__float2bfloat16_rn(v)); }
__device__ __forceinline__ uint32_t pack_bf16(float lo, float hi) {
    __nv_bfloat162 h = __floats2bfloat162_rn(lo, hi);
    return *reinterpret_cast<uint32_t*>(&h);
}
__device__ __forceinline__ float exp_neg(float v) {
    float r;
    asm("ex2.approx.ftz.f32 %0, %1;" : "=f"(r) : "f"(v * 1.4426950408889634f));
    return r;
}

__device__ __forceinline__ void rowsum_group(float (&acc)[12][4], uint32_t slot, const uint32_t (&off)[4], uint32_t b0, uint32_t b1) {
#pragma unroll
    for (int s = 0; s < 3; s++) {
        uint32_t a[4][4];
#pragma unroll
        for (int j = 0; j < 4; j++) ldsm4t(a[j], slot + off[j] + s * 128);
#pragma unroll
        for (int j = 0; j < 4; j++) mma16816(acc[s * 4 + j], a[j], b0, b1);
    }
}
__device__ __forceinline__ void rowsum_finish(const float (&acc)[12][4], float* red, int lane) {
    const int g = lane >> 2, t = lane & 3;
    const int from = (lane & ~3) | ((t + 3) & 3);
#pragma unroll
    for (int s = 0; s < 3; s++) {
        float val[8];
#pragma unroll
        for (int j = 0; j < 4; j++) {
            val[2 * j]     = acc[s * 4 + j][0] + acc[s * 4 + ((j + 3) & 3)][3];
            val[2 * j + 1] = acc[s * 4 + j][1] + acc[s * 4 + j][2];
        }
        float nw[4];
#pragma unroll
        for (int v = 0; v < 4; v++) nw[v] = val[v] + __shfl_xor_sync(0xffffffffu, val[v + 4], 2);
#pragma unroll
        for (int v = 0; v < 2; v++) red[64 * s + 8 * (2 * t + v) + g] = nw[v] + __shfl_sync(0xffffffffu, nw[v + 2], from);
    }
}
__device__ __forceinline__ void issue_wq(uint32_t ring, uint32_t full, const CUtensorMap* tm, int h, int r, int i) {
    mbar_expect_tx(full + 8 * i, i < 2 ? SLOT : SLOT / 2);
    tma_2d(ring + i * SLOT, tm, h * DH, r * XROWS + i * 64, full + 8 * i);
    if (i < 2) tma_2d(ring + i * SLOT + SLOT / 2, tm, h * DH, r * XROWS + i * 64 + 32, full + 8 * i);
}

__global__ void __launch_bounds__(NTHREADS, 1)
gqa_decode_kernel(const __nv_bfloat16* __restrict__ kc, const __nv_bfloat16* __restrict__ vc,
                  const __nv_bfloat16* __restrict__ x, __nv_bfloat16* __restrict__ out, Scratch* __restrict__ sc,
                  const __grid_constant__ CUtensorMap tm_wq, const __grid_constant__ CUtensorMap tm_wo) {
    extern __shared__ __align__(1024) unsigned char smem[];
    const int tid = threadIdx.x, warp = tid >> 5, lane = tid & 31;
    const int cta = blockIdx.x, h = cta >> 2, r = cta & 3;
    const uint32_t ring = smem_u32(smem) + SM_RING;
    const uint32_t full = smem_u32(smem) + SM_BARS, empty = full + NSLOT * 8;
    const unsigned char* kp = reinterpret_cast<const unsigned char*>(kc) + (size_t)cta * (TOK_CTA * ROWB);

    if (tid == 0) {
        mbar_init(full + 8 * IT_K, 1);
        mbar_init_fence();
        mbar_expect_tx(full + 8 * IT_K, SLOT);
        bulk_load(ring + IT_K * SLOT, kp, SLOT, full + 8 * IT_K);
#pragma unroll
        for (int i = 0; i < NSLOT; i++) if (i != IT_K) mbar_init(full + 8 * i, 1);
        mbar_init_fence();
        issue_wq(ring, full, &tm_wq, h, r, 0);
        issue_wq(ring, full, &tm_wq, h, r, 1);
#pragma unroll
        for (int i = 0; i < NSLOT; i++) mbar_init(empty + 8 * i, NCW + 1);
    }
    __syncthreads();
    const int g = lane >> 2, t = lane & 3;
    float* ml = reinterpret_cast<float*>(smem + SM_ML);

    if (warp == 0) {
        if (lane == 0) {
            const unsigned char* vp = reinterpret_cast<const unsigned char*>(vc) + (size_t)cta * (TOK_CTA * ROWB);
            asm volatile("prefetch.tensormap [%0];" :: "l"(&tm_wo) : "memory");
            wait_item(full, IT_K);
            issue_wq(ring, full, &tm_wq, h, r, 2);
            int landed = 0;
#pragma unroll 1
            for (int it = IT_K + 1; it < IT_END; it++) {
                const int s = (unsigned)it % NSLOT, n = it - IT_K;
                if (n >= PACE_FROM) {
                    const int need = it < IT_O ? NCTA * n + cta - PACE_KV
                                               : min(NCTA * n + cta - PACE_WO, NCTA * 2 * NTILE - PACE_MIN);
                    unsigned spins = 0;
                    while (landed < need) {
                        landed = ld_x(&sc->landed);
                        if (++spins > POLL_LIMIT) __trap();
                    }
                }
                if (it < HEAD_UNTIL) wait_item(full, it - WIN_HEAD <= IT_K ? it - WIN_HEAD - 1 : it - WIN_HEAD);
                if (it >= NSLOT) mbar_wait(empty + 8 * s, ((it / NSLOT) & 1) ^ 1);
                if (it < IT_O) {
                    mbar_expect_tx(full + 8 * s, SLOT);
                    bulk_load(ring + s * SLOT, it < IT_V ? kp + (size_t)n * SLOT : vp + (size_t)(it - IT_V) * SLOT, SLOT, full + 8 * s);
                } else {
                    mbar_expect_tx(full + 8 * s, WOB);
                    tma_3d(ring + s * SLOT, &tm_wo, 0, cta * OROWS + (it - IT_O) * 16, 0, full + 8 * s);
                }
            }
        }
        return;
    }

    if (warp == W_COUNT) {
        if (lane < IT_K) mbar_arrive(empty + 8 * lane);
#pragma unroll 1
        for (int it = IT_K; it < IT_O; it++) {
            wait_item(full, it);
            if (lane == 0) {
                count(&sc->landed);
                mbar_arrive(empty + 8 * ((unsigned)it % NSLOT));
            }
            if (it == IT_O - 2) bar_arrive(B_LATE, 64);
        }
        return;
    }

    if (warp == W_XCHG) {
        {
            const float* in = sc->x0 + cta * SPLIT * DH + 2 * lane;
            uint2 v[SPLIT][3];
            unsigned spins = 0, lo;
            do {
                lo = 0xffffffffu;
#pragma unroll
                for (int s = 0; s < SPLIT; s++)
#pragma unroll
                    for (int i = 0; i < 3; i++) v[s][i] = ld_x2(in + s * DH + i * 64);
#pragma unroll
                for (int s = 0; s < SPLIT; s++)
#pragma unroll
                    for (int i = 0; i < 3; i++) lo = min(lo, umin2(v[s][i]));
                if (++spins > POLL_LIMIT) __trap();
            } while (lo == 0);
            uint32_t* qw = reinterpret_cast<uint32_t*>(smem + SM_Q);
#pragma unroll
            for (int i = 0; i < 3; i++)
                qw[i * 32 + lane] = pack_bf16(sum4(f32(v[0][i].x), f32(v[1][i].x), f32(v[2][i].x), f32(v[3][i].x)),
                                              sum4(f32(v[0][i].y), f32(v[1][i].y), f32(v[2][i].y), f32(v[3][i].y)));
            __syncwarp();
            bar_arrive(B_Q, N_CX);
#pragma unroll
            for (int i = 0; i < SPLIT * DH / 128; i++) st_zero4(sc->x0 + cta * SPLIT * DH + i * 128 + lane * 4);
        }
        {
            unsigned spins = 0;
            while (ld_x(&sc->cleared) < NCTA) if (++spins > POLL_LIMIT) __trap();
            fence_gpu();
        }
        {
            bar_sync(B_L, N_CX);
            const float m = fmaxf(fmaxf(ml[0], ml[1]), fmaxf(ml[2], ml[3]));
            const float l = sum4(ml[4], ml[5], ml[6], ml[7]);
            if (lane < 2 * SPLIT) st_x4(sc->xm + ((h * SPLIT + (lane >> 1)) * SPLIT + r) * 8 + (lane & 1) * 4, make_float4(m, l, m, l));
            const float* in = sc->xm + (cta * SPLIT + (lane & 3)) * 8;
            uint2 v;
            unsigned spins = 0;
            do {
                v = ld_x2(in);
                if (++spins > POLL_LIMIT) __trap();
            } while (umin2(v) == 0);
            __syncwarp();
            float mm = fmaxf(f32(v.x), __shfl_xor_sync(0xffffffffu, f32(v.x), 1));
            mm = fmaxf(mm, __shfl_xor_sync(0xffffffffu, mm, 2));
            float ll = f32(v.y) * exp_neg(f32(v.x) - mm);
            ll += __shfl_xor_sync(0xffffffffu, ll, 1);
            ll += __shfl_xor_sync(0xffffffffu, ll, 2);
            if (lane == 0) ml[8] = exp_neg(m - mm) / ll;
            bar_arrive(B_F, N_CX);
        }
        {
            bar_sync(B_LATE, 64);
            const int j = lane < 24 ? lane : 0;
            const float* in = sc->x1 + cta * SPLIT * OROWS + 2 * j;
            uint2 v[SPLIT];
            unsigned spins = 0;
            do {
#pragma unroll
                for (int s = 0; s < SPLIT; s++) v[s] = ld_x2(in + s * OROWS);
                if (++spins > POLL_LIMIT) __trap();
            } while (min(min(umin2(v[0]), umin2(v[1])), min(umin2(v[2]), umin2(v[3]))) == 0);
            if (lane < 24)
                reinterpret_cast<uint32_t*>(smem + SM_O)[(j >> 3) * 8 + (j & 3) * 2 + ((j >> 2) & 1)] =
                    pack_bf16(sum4(f32(v[0].x), f32(v[1].x), f32(v[2].x), f32(v[3].x)), sum4(f32(v[0].y), f32(v[1].y), f32(v[2].y), f32(v[3].y)));
            bar_arrive(B_O, N_CX);
        }
        return;
    }

    if (warp == W_RED) {
        float* p = sc->x2 + cta * NCTA * 8 + lane * 4;
        st_zero4(sc->x1 + cta * SPLIT * OROWS + lane * 4);
        if (lane < 16) st_zero4(sc->x1 + cta * SPLIT * OROWS + 128 + lane * 4);
        if (lane < 2 * SPLIT) st_zero4(sc->xm + cta * SPLIT * 8 + lane * 4);
        if (cta < NRED) {
#pragma unroll
            for (int i = 0; i < 8; i++) st_zero4(p + i * 128);
        }
        __syncwarp();
        if (lane == 0) {
            fence_gpu();
            count(&sc->cleared);
        }
        if (cta >= NRED) return;
        __nv_bfloat16* po = out + cta * 8 + (lane & 1) * 4 + (lane >> 3);
        bar_sync(B_Y, N_CX);
        uint4 v[8];
#pragma unroll
        for (int i = 0; i < 8; i++) v[i] = ld_x4(p + i * 128);
        unsigned spins = 0;
        while (!__all_sync(0xffffffffu, min(min(min(umin4(v[0]), umin4(v[1])), min(umin4(v[2]), umin4(v[3]))),
                                            min(min(umin4(v[4]), umin4(v[5])), min(umin4(v[6]), umin4(v[7])))) != 0)) {
#pragma unroll
            for (int i = 0; i < 8; i++) if (umin4(v[i]) == 0) v[i] = ld_x4(p + i * 128);
            if (++spins > POLL_LIMIT) __trap();
        }
        const float s0 = sum4(f32(v[0].x), f32(v[1].x), f32(v[2].x), f32(v[3].x)) + sum4(f32(v[4].x), f32(v[5].x), f32(v[6].x), f32(v[7].x));
        const float s1 = sum4(f32(v[0].y), f32(v[1].y), f32(v[2].y), f32(v[3].y)) + sum4(f32(v[4].y), f32(v[5].y), f32(v[6].y), f32(v[7].y));
        const float s2 = sum4(f32(v[0].z), f32(v[1].z), f32(v[2].z), f32(v[3].z)) + sum4(f32(v[4].z), f32(v[5].z), f32(v[6].z), f32(v[7].z));
        const float s3 = sum4(f32(v[0].w), f32(v[1].w), f32(v[2].w), f32(v[3].w)) + sum4(f32(v[4].w), f32(v[5].w), f32(v[6].w), f32(v[7].w));
        const bool up = lane & 16, up2 = lane & 8;
        const float a0 = (up ? s2 : s0) + __shfl_xor_sync(0xffffffffu, up ? s0 : s2, 16);
        const float a1 = (up ? s3 : s1) + __shfl_xor_sync(0xffffffffu, up ? s1 : s3, 16);
        float b = (up2 ? a1 : a0) + __shfl_xor_sync(0xffffffffu, up2 ? a0 : a1, 8);
        b += __shfl_xor_sync(0xffffffffu, b, 4);
        b += __shfl_xor_sync(0xffffffffu, b, 2);
        if ((lane & 6) == 0) *po = __float2bfloat16_rn(b);
        if (cta == 0 && lane < 2) asm volatile("st.relaxed.gpu.global.b32 [%0], %1;" :: "l"(&sc->landed + 32 * lane), "r"(0) : "memory");
        return;
    }

    const int cw = warp - 1;
    const bool diag = (t == (g >> 1));
    const uint32_t sel0 = diag ? ((g & 1) ? 0x1044u : 0x4410u) : 0x4444u;
    const uint32_t sel1 = diag ? ((g & 1) ? 0x3244u : 0x4432u) : 0x4444u;
    uint32_t offk[4], offv[4];
    {
        const int mi = lane >> 3, rr = lane & 7;
#pragma unroll
        for (int j = 0; j < 4; j++) {
            offk[j] = cw * GRP + (rr + 8 * (mi & 1)) * ROWB + ((2 * j + (mi >> 1) + rr) & 7) * 16;
            offv[j] = cw * GRP + (rr + 8 * (mi >> 1)) * ROWB + ((2 * j + (mi & 1) + rr) & 7) * 16;
        }
    }
    float* red = reinterpret_cast<float*>(smem + SM_RED);
    uint32_t* pw = reinterpret_cast<uint32_t*>(smem + SM_P) + cw * (NTILE * 8);
    auto release = [&](int s) { __syncwarp(); if (lane == 0) mbar_arrive(empty + 8 * s); };

    float acc[12][4];
    {
        const int nq = cw < 2 ? 3 : 2;
        uint32_t xw[3];
#pragma unroll
        for (int i = 0; i < 3; i++) {
            xw[i] = 0;
            if (i < nq) {
                const unsigned short* xs = reinterpret_cast<const unsigned short*>(x) + r * XROWS + (cw + 4 * i) * 16 + g;
                xw[i] = (uint32_t)__ldg(xs) | ((uint32_t)__ldg(xs + 8) << 16);
            }
        }
#pragma unroll
        for (int i = 0; i < 12; i++) { acc[i][0] = acc[i][1] = acc[i][2] = acc[i][3] = 0.f; }
#pragma unroll 1
        for (int i = 0; i < 3; i++) {
            const uint32_t w = i == 0 ? xw[0] : (i == 1 ? xw[1] : xw[2]);
            wait_item(full, i);
            if (i < nq) rowsum_group(acc, ring + i * SLOT, offv, __byte_perm(w, 0, sel0), __byte_perm(w, 0, sel1));
            release(i);
        }
        rowsum_finish(acc, red + cw * DH, lane);
        bar_sync(B_CONS, NCW * 32);
        const float2* r2 = reinterpret_cast<const float2*>(red);
        float* dst = sc->x0 + ((h * SPLIT + cw) * SPLIT + r) * DH + 2 * lane;
#pragma unroll
        for (int i = 0; i < 3; i++) {
            const float2 a = r2[i * 32 + lane], b = r2[DH / 2 + i * 32 + lane], c = r2[DH + i * 32 + lane], d = r2[3 * DH / 2 + i * 32 + lane];
            st_x2(dst + i * 64, sum4(a.x, b.x, c.x, d.x), sum4(a.y, b.y, c.y, d.y));
        }
        bar_sync(B_Q, N_CX);
    }

    float mx = -INFINITY;
    {
        const uint32_t* qw = reinterpret_cast<const uint32_t*>(smem + SM_Q);
        uint32_t qb[3][8];
#pragma unroll
        for (int s = 0; s < 3; s++)
#pragma unroll
            for (int u = 0; u < 8; u++) qb[s][u] = qw[32 * s + 4 * ((u + g) & 7) + t];
        const float scale = 0.07216878364870322f;
#pragma unroll 1
        for (int i = 0; i < NTILE; i++) {
            const int slot = (unsigned)(IT_K + i) % NSLOT;
            wait_item(full, IT_K + i);
            const uint32_t sa = ring + slot * SLOT;
            float c[3][4];
#pragma unroll
            for (int s = 0; s < 3; s++) {
                uint32_t a[4][4];
                c[s][0] = c[s][1] = c[s][2] = c[s][3] = 0.f;
#pragma unroll
                for (int j = 0; j < 4; j++) ldsm4(a[j], sa + offk[j] + s * 128);
#pragma unroll
                for (int j = 0; j < 4; j++) mma16816(c[s], a[j], qb[s][2 * j], qb[s][2 * j + 1]);
            }
            release(slot);
            const bool odd = g & 1;
            float lo = odd ? (c[0][1] + c[1][1]) + c[2][1] : (c[0][0] + c[1][0]) + c[2][0];
            float hi = odd ? (c[0][3] + c[1][3]) + c[2][3] : (c[0][2] + c[1][2]) + c[2][2];
            lo = bf16r(bf16r(lo) * scale);
            hi = bf16r(bf16r(hi) * scale);
            if (diag) {
                mx = fmaxf(mx, fmaxf(lo, hi));
                pw[i * 8 + g] = pack_bf16(lo, hi);
            }
        }
    }
    {
#pragma unroll
        for (int o = 16; o > 0; o >>= 1) mx = fmaxf(mx, __shfl_xor_sync(0xffffffffu, mx, o));
        if (lane == 0) ml[cw] = mx;
        bar_sync(B_CONS, NCW * 32);
        mx = fmaxf(fmaxf(ml[0], ml[1]), fmaxf(ml[2], ml[3]));
        float lsum = 0.f;
#pragma unroll
        for (int i = 0; i < NTILE * 8 / 32; i++) {
            const uint32_t w = pw[i * 32 + lane];
            const float e0 = exp_neg(f32(w << 16) - mx), e1 = exp_neg(f32(w & 0xffff0000u) - mx);
            lsum += e0 + e1;
            pw[i * 32 + lane] = pack_bf16(e0, e1);
        }
#pragma unroll
        for (int o = 16; o > 0; o >>= 1) lsum += __shfl_xor_sync(0xffffffffu, lsum, o);
        if (lane == 0) ml[4 + cw] = lsum;
        __syncwarp();
        bar_arrive(B_L, N_CX);
    }
#pragma unroll
    for (int i = 0; i < 12; i++) { acc[i][0] = acc[i][1] = acc[i][2] = acc[i][3] = 0.f; }
#pragma unroll 1
    for (int i = 0; i < NTILE; i++) {
        const int slot = (unsigned)(IT_V + i) % NSLOT;
        const uint32_t w = pw[i * 8 + g];
        wait_item(full, IT_V + i);
        rowsum_group(acc, ring + slot * SLOT, offv, __byte_perm(w, 0, sel0), __byte_perm(w, 0, sel1));
        release(slot);
    }
    rowsum_finish(acc, red + cw * DH, lane);
    bar_sync(B_F, N_CX);
    if (lane < 12) {
        const float f = ml[8];
        const float4* r4 = reinterpret_cast<const float4*>(red) + cw * 12 + lane;
        const float4 a = r4[0], b = r4[DH / 4], c = r4[2 * DH / 4], d = r4[3 * DH / 4];
        st_x4(sc->x1 + ((h * SPLIT + cw) * SPLIT + r) * OROWS + lane * 4,
              make_float4(sum4(a.x, b.x, c.x, d.x) * f, sum4(a.y, b.y, c.y, d.y) * f, sum4(a.z, b.z, c.z, d.z) * f, sum4(a.w, b.w, c.w, d.w) * f));
    }
    __syncwarp();
    {
        uint32_t offw = ring + ((lane & 7) + 8 * (lane >> 4)) * 128 + (((2 * cw + ((lane >> 3) & 1)) ^ (lane & 7)) * 16);
        float* dst = sc->x2 + ((8 * (t >> 1) + 2 * cw + (t & 1)) * NCTA + cta) * 8 + g;
        asm volatile("" : "+r"(offw), "+l"(dst));
        constexpr int S0 = IT_O % NSLOT, S1 = (IT_O + 1) % NSLOT, S2 = (IT_O + 2) % NSLOT;
        uint32_t a0[10][4], a1[10][4], a2[10][4];
        wait_item(full, IT_O);
#pragma unroll
        for (int b = 0; b < 10; b++) ldsm4t(a0[b], offw + b * 2048 + S0 * SLOT);
        wait_item(full, IT_O + 1);
#pragma unroll
        for (int b = 0; b < 10; b++) ldsm4t(a1[b], offw + b * 2048 + S1 * SLOT);
        bar_sync(B_O, N_CX);
        uint2 ob[3];
#pragma unroll
        for (int ks = 0; ks < 3; ks++) ob[ks] = reinterpret_cast<const uint2*>(smem + SM_O)[ks * 4 + t];
        const bool early = __all_sync(0xffffffffu, mbar_test(full + 8 * S2, ((IT_O + 2) / NSLOT) & 1));
        float y[10][4];
#pragma unroll
        for (int b = 0; b < 10; b++) { y[b][0] = y[b][1] = y[b][2] = y[b][3] = 0.f; }
        if (early) {
#pragma unroll
            for (int b = 0; b < 10; b++) ldsm4t(a2[b], offw + b * 2048 + S2 * SLOT);
        }
#pragma unroll
        for (int b = 0; b < 10; b++) mma16816(y[b], a0[b], ob[0].x, ob[0].y);
#pragma unroll
        for (int b = 0; b < 10; b++) mma16816(y[b], a1[b], ob[1].x, ob[1].y);
        if (!early) {
            wait_item(full, IT_O + 2);
#pragma unroll
            for (int b = 0; b < 10; b++) ldsm4t(a2[b], offw + b * 2048 + S2 * SLOT);
        }
#pragma unroll
        for (int b = 0; b < 10; b++) mma16816(y[b], a2[b], ob[2].x, ob[2].y);
#pragma unroll
        for (int i = 0; i < 5; i++) {
            const float v = (t & 2) ? ((t & 1) ? y[2 * i + 1][2] : y[2 * i + 1][0]) : ((t & 1) ? y[2 * i][2] : y[2 * i][0]);
            st_x(dst + i * 16 * NCTA * 8, v);
        }
        if (cta < NRED) bar_arrive(B_Y, N_CX);
    }
}

typedef CUresult (*EncodeTiledFn)(CUtensorMap*, CUtensorMapDataType, cuuint32_t, void*, const cuuint64_t*, const cuuint64_t*,
                                  const cuuint32_t*, const cuuint32_t*, CUtensorMapInterleave, CUtensorMapSwizzle,
                                  CUtensorMapL2promotion, CUtensorMapFloatOOBfill);

}

extern "C" void kernel_launch(void* const* d_in, const int* in_sizes, int n_in, void* d_out, int out_size) {
    (void)in_sizes; (void)n_in; (void)out_size;
    using namespace gqa;
    static EncodeTiledFn encode = nullptr;
    static Scratch* scratch = nullptr;
    if (!encode) {
        cudaGetSymbolAddress((void**)&scratch, g_scratch);
        void* fn = nullptr;
        cudaDriverEntryPointQueryResult qr;
        cudaGetDriverEntryPoint("cuTensorMapEncodeTiled", &fn, cudaEnableDefault, &qr);
        encode = (EncodeTiledFn)fn;
        cudaFuncSetAttribute(gqa_decode_kernel, cudaFuncAttributeMaxDynamicSharedMemorySize, SM_TOTAL);
    }
    CUtensorMap tm_wq, tm_wo;
    {
        cuuint64_t dims[2] = {QCOLS, D_MODEL}, strides[1] = {QCOLS * 2};
        cuuint32_t box[2] = {DH, 32}, es[2] = {1, 1};
        encode(&tm_wq, CU_TENSOR_MAP_DATA_TYPE_BFLOAT16, 2, d_in[3], dims, strides, box, es, CU_TENSOR_MAP_INTERLEAVE_NONE,
               CU_TENSOR_MAP_SWIZZLE_NONE, CU_TENSOR_MAP_L2_PROMOTION_NONE, CU_TENSOR_MAP_FLOAT_OOB_FILL_NONE);
    }
    {
        cuuint64_t dims[3] = {64, QCOLS, D_MODEL / 64}, strides[2] = {D_MODEL * 2, 128};
        cuuint32_t box[3] = {64, 16, D_MODEL / 64}, es[3] = {1, 1, 1};
        encode(&tm_wo, CU_TENSOR_MAP_DATA_TYPE_BFLOAT16, 3, d_in[4], dims, strides, box, es, CU_TENSOR_MAP_INTERLEAVE_NONE,
               CU_TENSOR_MAP_SWIZZLE_128B, CU_TENSOR_MAP_L2_PROMOTION_NONE, CU_TENSOR_MAP_FLOAT_OOB_FILL_NONE);
    }
    gqa_decode_kernel<<<NCTA, NTHREADS, SM_TOTAL>>>((const __nv_bfloat16*)d_in[1], (const __nv_bfloat16*)d_in[2],
                                                    (const __nv_bfloat16*)d_in[0], (__nv_bfloat16*)d_out, scratch, tm_wq, tm_wo);
}
```

```cpp
#include <cuda_runtime.h>
#include <cuda.h>
#include <cuda_bf16.h>
#include <stdint.h>

namespace gqa {

constexpr int D_MODEL = 640;
constexpr int NH      = 32;
constexpr int SK      = 8192;
constexpr int DH      = 192;
constexpr int QCOLS   = NH * DH;
constexpr int SPLIT   = 4;
constexpr int NCTA    = NH * SPLIT;
constexpr int NCW     = 4;
constexpr int W_XCHG = NCW + 1, W_COUNT = NCW + 2, W_RED = NCW + 3;
constexpr int NTHREADS = (NCW + 4) * 32;
constexpr int TOK_CTA = SK / SPLIT;
constexpr int NTILE   = TOK_CTA / 64;
constexpr int ROWB    = DH * 2;
constexpr int GRP     = 16 * ROWB;
constexpr int SLOT    = NCW * GRP;
constexpr int NSLOT   = 8;
constexpr int XROWS   = D_MODEL / SPLIT;
constexpr int OROWS   = DH / SPLIT;
constexpr int WOB     = 16 * D_MODEL * 2;
constexpr int NRED    = D_MODEL / 8;
constexpr int IT_K = 3, IT_V = IT_K + NTILE, IT_O = IT_V + NTILE, IT_END = IT_O + 3;

constexpr int WIN_HEAD = 3, HEAD_UNTIL = NSLOT + IT_K;
constexpr int PACE_FROM = 48, PACE_KV = 640, PACE_WO = 384, PACE_MIN = 32;

constexpr int SM_RING = 0;
constexpr int SM_BARS = SM_RING + NSLOT * SLOT;
constexpr int SM_P    = SM_BARS + 128;
constexpr int SM_RED  = SM_P + NCW * NTILE * 8 * 4;
constexpr int SM_ML   = SM_RED + NCW * DH * 4;
constexpr int SM_Q    = SM_ML + 64;
constexpr int SM_O    = SM_Q + DH * 2;
constexpr int SM_TOTAL = SM_O + 128;
constexpr int B_CONS = 1, B_Q = 2, B_L = 3, B_F = 4, B_LATE = 5, B_O = 6, B_Y = 7;
constexpr int N_CX = (NCW + 1) * 32;

constexpr unsigned MBAR_LIMIT = 1u << 19, POLL_LIMIT = 1u << 22;

struct Scratch {
    float x2[NRED * NCTA * 8];
    float x0[NCTA * DH];
    float x1[NCTA * SPLIT * OROWS];
    float xm[NCTA * SPLIT * 8];
    unsigned landed;
    unsigned pad[31];
    unsigned cleared;
};
__device__ __align__(128) Scratch g_scratch;

__device__ __forceinline__ uint32_t smem_u32(const void* p) { return (uint32_t)__cvta_generic_to_shared(p); }

__device__ __forceinline__ void mbar_init(uint32_t bar, uint32_t cnt) {
    asm volatile("mbarrier.init.shared::cta.b64 [%0], %1;" :: "r"(bar), "r"(cnt) : "memory");
}
__device__ __forceinline__ void mbar_init_fence() { asm volatile("fence.mbarrier_init.release.cluster;" ::: "memory"); }
__device__ __forceinline__ void mbar_expect_tx(uint32_t bar, uint32_t bytes) {
    asm volatile("mbarrier.arrive.expect_tx.shared::cta.b64 _, [%0], %1;" :: "r"(bar), "r"(bytes) : "memory");
}
__device__ __forceinline__ void mbar_arrive(uint32_t bar) {
    asm volatile("mbarrier.arrive.shared::cta.b64 _, [%0];" :: "r"(bar) : "memory");
}
__device__ __forceinline__ bool mbar_try(uint32_t bar, uint32_t parity) {
    uint32_t ok;
    asm volatile("{\n.reg .pred p;\nmbarrier.try_wait.parity.shared::cta.b64 p, [%1], %2;\nselp.u32 %0, 1, 0, p;\n}"
                 : "=r"(ok) : "r"(bar), "r"(parity) : "memory");
    return ok;
}
__device__ __forceinline__ bool mbar_test(uint32_t bar, uint32_t parity) {
    uint32_t ok;
    asm volatile("{\n.reg .pred p;\nmbarrier.test_wait.parity.shared::cta.b64 p, [%1], %2;\nselp.u32 %0, 1, 0, p;\n}"
                 : "=r"(ok) : "r"(bar), "r"(parity) : "memory");
    return ok;
}
__device__ __forceinline__ void mbar_wait(uint32_t bar, uint32_t parity) {
    if (mbar_try(bar, parity)) return;
    unsigned spins = 0;
    while (!mbar_try(bar, parity)) if (++spins > MBAR_LIMIT) __trap();
}
__device__ __forceinline__ void wait_item(uint32_t full, unsigned it) { mbar_wait(full + 8 * (it % NSLOT), (it / NSLOT) & 1); }

constexpr uint64_t STREAM = 0x12F0000000000000ull;
__device__ __forceinline__ void bulk_load(uint32_t dst, const void* src, uint32_t bytes, uint32_t bar) {
    asm volatile("cp.async.bulk.shared::cluster.global.mbarrier::complete_tx::bytes.L2::cache_hint [%0], [%1], %2, [%3], %4;"
                 :: "r"(dst), "l"(src), "r"(bytes), "r"(bar), "l"(STREAM) : "memory");
}
__device__ __forceinline__ void tma_2d(uint32_t dst, const CUtensorMap* tm, int c0, int c1, uint32_t bar) {
    asm volatile("cp.async.bulk.tensor.2d.shared::cluster.global.mbarrier::complete_tx::bytes.L2::cache_hint [%0], [%1, {%3, %4}], [%2], %5;"
                 :: "r"(dst), "l"(tm), "r"(bar), "r"(c0), "r"(c1), "l"(STREAM) : "memory");
}
__device__ __forceinline__ void tma_3d(uint32_t dst, const CUtensorMap* tm, int c0, int c1, int c2, uint32_t bar) {
    asm volatile("cp.async.bulk.tensor.3d.shared::cluster.global.mbarrier::complete_tx::bytes.L2::cache_hint [%0], [%1, {%3, %4, %5}], [%2], %6;"
                 :: "r"(dst), "l"(tm), "r"(bar), "r"(c0), "r"(c1), "r"(c2), "l"(STREAM) : "memory");
}
__device__ __forceinline__ void ldsm4(uint32_t (&a)[4], uint32_t addr) {
    asm volatile("ldmatrix.sync.aligned.m8n8.x4.shared.b16 {%0,%1,%2,%3}, [%4];"
                 : "=r"(a[0]), "=r"(a[1]), "=r"(a[2]), "=r"(a[3]) : "r"(addr) : "memory");
}
__device__ __forceinline__ void ldsm4t(uint32_t (&a)[4], uint32_t addr) {
    asm volatile("ldmatrix.sync.aligned.m8n8.x4.trans.shared.b16 {%0,%1,%2,%3}, [%4];"
                 : "=r"(a[0]), "=r"(a[1]), "=r"(a[2]), "=r"(a[3]) : "r"(addr) : "memory");
}
__device__ __forceinline__ void mma16816(float (&c)[4], const uint32_t (&a)[4], uint32_t b0, uint32_t b1) {
    asm volatile("mma.sync.aligned.m16n8k16.row.col.f32.bf16.bf16.f32 {%0,%1,%2,%3}, {%4,%5,%6,%7}, {%8,%9}, {%0,%1,%2,%3};"
                 : "+f"(c[0]), "+f"(c[1]), "+f"(c[2]), "+f"(c[3])
                 : "r"(a[0]), "r"(a[1]), "r"(a[2]), "r"(a[3]), "r"(b0), "r"(b1));
}
__device__ __forceinline__ void bar_sync(int id, int n) { asm volatile("bar.sync %0, %1;" :: "r"(id), "r"(n) : "memory"); }
__device__ __forceinline__ void bar_arrive(int id, int n) { asm volatile("bar.arrive %0, %1;" :: "r"(id), "r"(n) : "memory"); }
__device__ __forceinline__ void fence_gpu() { asm volatile("fence.acq_rel.gpu;" ::: "memory"); }

__device__ __forceinline__ uint32_t enc(float v) { uint32_t u = __float_as_uint(v); return u ? u : 0x80000000u; }
__device__ __forceinline__ void st_x(float* p, float v) {
    asm volatile("st.relaxed.gpu.global.b32 [%0], %1;" :: "l"(p), "r"(enc(v)) : "memory");
}
__device__ __forceinline__ void st_x2(float* p, float a, float b) {
    asm volatile("st.relaxed.gpu.global.v2.b32 [%0], {%1,%2};" :: "l"(p), "r"(enc(a)), "r"(enc(b)) : "memory");
}
__device__ __forceinline__ void st_x4(float* p, float4 v) {
    asm volatile("st.relaxed.gpu.global.v4.b32 [%0], {%1,%2,%3,%4};"
                 :: "l"(p), "r"(enc(v.x)), "r"(enc(v.y)), "r"(enc(v.z)), "r"(enc(v.w)) : "memory");
}
__device__ __forceinline__ void st_zero4(float* p) {
    asm volatile("st.relaxed.gpu.global.v4.b32 [%0], {%1,%1,%1,%1};" :: "l"(p), "r"(0) : "memory");
}
__device__ __forceinline__ uint32_t ld_x(const unsigned* p) {
    uint32_t v;
    asm volatile("ld.relaxed.gpu.global.b32 %0, [%1];" : "=r"(v) : "l"(p) : "memory");
    return v;
}
__device__ __forceinline__ uint2 ld_x2(const float* p) {
    uint2 v;
    asm volatile("ld.relaxed.gpu.global.v2.b32 {%0,%1}, [%2];" : "=r"(v.x), "=r"(v.y) : "l"(p) : "memory");
    return v;
}
__device__ __forceinline__ uint4 ld_x4(const float* p) {
    uint4 v;
    asm volatile("ld.relaxed.gpu.global.v4.b32 {%0,%1,%2,%3}, [%4];" : "=r"(v.x), "=r"(v.y), "=r"(v.z), "=r"(v.w) : "l"(p) : "memory");
    return v;
}
__device__ __forceinline__ void count(unsigned* p) { asm volatile("red.relaxed.gpu.global.add.u32 [%0], 1;" :: "l"(p) : "memory"); }
__device__ __forceinline__ uint32_t umin2(uint2 v) { return min(v.x, v.y); }
__device__ __forceinline__ uint32_t umin4(uint4 v) { return min(min(v.x, v.y), min(v.z, v.w)); }
__device__ __forceinline__ float f32(uint32_t u) { return __uint_as_float(u); }
__device__ __forceinline__ float sum4(float a, float b, float c, float d) { return (a + b) + (c + d); }

__device__ __forceinline__ float bf16r(float v) { return __bfloat162float(__float2bfloat16_rn(v)); }
__device__ __forceinline__ uint32_t pack_bf16(float lo, float hi) {
    __nv_bfloat162 h = __floats2bfloat162_rn(lo, hi);
    return *reinterpret_cast<uint32_t*>(&h);
}
__device__ __forceinline__ float exp_neg(float v) {
    float r;
    asm("ex2.approx.ftz.f32 %0, %1;" : "=f"(r) : "f"(v * 1.4426950408889634f));
    return r;
}

__device__ __forceinline__ void rowsum_group(float (&acc)[12][4], uint32_t slot, const uint32_t (&off)[4], uint32_t b0, uint32_t b1) {
#pragma unroll
    for (int s = 0; s < 3; s++) {
        uint32_t a[4][4];
#pragma unroll
        for (int j = 0; j < 4; j++) ldsm4t(a[j], slot + off[j] + s * 128);
#pragma unroll
        for (int j = 0; j < 4; j++) mma16816(acc[s * 4 + j], a[j], b0, b1);
    }
}
__device__ __forceinline__ void rowsum_finish(const float (&acc)[12][4], float* red, int lane) {
    const int g = lane >> 2, t = lane & 3;
    const int from = (lane & ~3) | ((t + 3) & 3);
#pragma unroll
    for (int s = 0; s < 3; s++) {
        float val[8];
#pragma unroll
        for (int j = 0; j < 4; j++) {
            val[2 * j]     = acc[s * 4 + j][0] + acc[s * 4 + ((j + 3) & 3)][3];
            val[2 * j + 1] = acc[s * 4 + j][1] + acc[s * 4 + j][2];
        }
        float nw[4];
#pragma unroll
        for (int v = 0; v < 4; v++) nw[v] = val[v] + __shfl_xor_sync(0xffffffffu, val[v + 4], 2);
#pragma unroll
        for (int v = 0; v < 2; v++) red[64 * s + 8 * (2 * t + v) + g] = nw[v] + __shfl_sync(0xffffffffu, nw[v + 2], from);
    }
}
__device__ __forceinline__ void issue_wq(uint32_t ring, uint32_t full, const CUtensorMap* tm, int h, int r, int i) {
    mbar_expect_tx(full + 8 * i, i < 2 ? SLOT : SLOT / 2);
    tma_2d(ring + i * SLOT, tm, h * DH, r * XROWS + i * 64, full + 8 * i);
    if (i < 2) tma_2d(ring + i * SLOT + SLOT / 2, tm, h * DH, r * XROWS + i * 64 + 32, full + 8 * i);
}

__global__ void __launch_bounds__(NTHREADS, 1)
gqa_decode_kernel(const __nv_bfloat16* __restrict__ kc, const __nv_bfloat16* __restrict__ vc,
                  const __nv_bfloat16* __restrict__ x, __nv_bfloat16* __restrict__ out, Scratch* __restrict__ sc,
                  const __grid_constant__ CUtensorMap tm_wq, const __grid_constant__ CUtensorMap tm_wo) {
    extern __shared__ __align__(1024) unsigned char smem[];
    const int tid = threadIdx.x, warp = tid >> 5, lane = tid & 31;
    const int cta = blockIdx.x, h = cta >> 2, r = cta & 3;
    const uint32_t ring = smem_u32(smem) + SM_RING;
    const uint32_t full = smem_u32(smem) + SM_BARS, empty = full + NSLOT * 8;
    const unsigned char* kp = reinterpret_cast<const unsigned char*>(kc) + (size_t)cta * (TOK_CTA * ROWB);

    if (tid == 0) {
        mbar_init(full + 8 * IT_K, 1);
        mbar_init_fence();
        mbar_expect_tx(full + 8 * IT_K, SLOT);
        bulk_load(ring + IT_K * SLOT, kp, SLOT, full + 8 * IT_K);
#pragma unroll
        for (int i = 0; i < NSLOT; i++) if (i != IT_K) mbar_init(full + 8 * i, 1);
        mbar_init_fence();
        issue_wq(ring, full, &tm_wq, h, r, 0);
        issue_wq(ring, full, &tm_wq, h, r, 1);
#pragma unroll
        for (int i = 0; i < NSLOT; i++) mbar_init(empty + 8 * i, NCW + 1);
    }
    __syncthreads();
    const int g = lane >> 2, t = lane & 3;
    float* ml = reinterpret_cast<float*>(smem + SM_ML);

    if (warp == 0) {
        if (lane == 0) {
            const unsigned char* vp = reinterpret_cast<const unsigned char*>(vc) + (size_t)cta * (TOK_CTA * ROWB);
            asm volatile("prefetch.tensormap [%0];" :: "l"(&tm_wo) : "memory");
            wait_item(full, IT_K);
            issue_wq(ring, full, &tm_wq, h, r, 2);
            int landed = 0;
#pragma unroll 1
            for (int it = IT_K + 1; it < IT_END; it++) {
                const int s = (unsigned)it % NSLOT, n = it - IT_K;
                if (n >= PACE_FROM) {
                    const int need = it < IT_O ? NCTA * n + cta - PACE_KV
                                               : min(NCTA * n + cta - PACE_WO, NCTA * 2 * NTILE - PACE_MIN);
                    unsigned spins = 0;
                    while (landed < need) {
                        landed = ld_x(&sc->landed);
                        if (++spins > POLL_LIMIT) __trap();
                    }
                }
                if (it < HEAD_UNTIL) wait_item(full, it - WIN_HEAD <= IT_K ? it - WIN_HEAD - 1 : it - WIN_HEAD);
                if (it >= NSLOT) mbar_wait(empty + 8 * s, ((it / NSLOT) & 1) ^ 1);
                if (it < IT_O) {
                    mbar_expect_tx(full + 8 * s, SLOT);
                    bulk_load(ring + s * SLOT, it < IT_V ? kp + (size_t)n * SLOT : vp + (size_t)(it - IT_V) * SLOT, SLOT, full + 8 * s);
                } else {
                    mbar_expect_tx(full + 8 * s, WOB);
                    tma_3d(ring + s * SLOT, &tm_wo, 0, cta * OROWS + (it - IT_O) * 16, 0, full + 8 * s);
                }
            }
        }
        return;
    }

    if (warp == W_COUNT) {
        if (lane < IT_K) mbar_arrive(empty + 8 * lane);
#pragma unroll 1
        for (int it = IT_K; it < IT_O; it++) {
            wait_item(full, it);
            if (lane == 0) {
                count(&sc->landed);
                mbar_arrive(empty + 8 * ((unsigned)it % NSLOT));
            }
            if (it == IT_O - 2) bar_arrive(B_LATE, 64);
        }
        return;
    }

    if (warp == W_XCHG) {
        {
            const float* in = sc->x0 + h * SPLIT * DH + 2 * lane;
            uint2 v[SPLIT][3];
            unsigned spins = 0, lo;
            do {
                lo = 0xffffffffu;
#pragma unroll
                for (int s = 0; s < SPLIT; s++)
#pragma unroll
                    for (int i = 0; i < 3; i++) v[s][i] = ld_x2(in + s * DH + i * 64);
#pragma unroll
                for (int s = 0; s < SPLIT; s++)
#pragma unroll
                    for (int i = 0; i < 3; i++) lo = min(lo, umin2(v[s][i]));
                if (++spins > POLL_LIMIT) __trap();
            } while (lo == 0);
            uint32_t* qw = reinterpret_cast<uint32_t*>(smem + SM_Q);
#pragma unroll
            for (int i = 0; i < 3; i++)
                qw[i * 32 + lane] = pack_bf16(sum4(f32(v[0][i].x), f32(v[1][i].x), f32(v[2][i].x), f32(v[3][i].x)),
                                              sum4(f32(v[0][i].y), f32(v[1][i].y), f32(v[2][i].y), f32(v[3][i].y)));
            bar_arrive(B_Q, N_CX);
        }
        {
            unsigned spins = 0;
            while (ld_x(&sc->cleared) < NCTA) if (++spins > POLL_LIMIT) __trap();
            fence_gpu();
        }
        {
            bar_sync(B_L, N_CX);
            const float m = fmaxf(fmaxf(ml[0], ml[1]), fmaxf(ml[2], ml[3]));
            const float l = sum4(ml[4], ml[5], ml[6], ml[7]);
            if (lane < 2 * SPLIT) st_x4(sc->xm + ((h * SPLIT + (lane >> 1)) * SPLIT + r) * 8 + (lane & 1) * 4, make_float4(m, l, m, l));
            const float* in = sc->xm + (cta * SPLIT + (lane & 3)) * 8;
            uint2 v;
            unsigned spins = 0;
            do {
                v = ld_x2(in);
                if (++spins > POLL_LIMIT) __trap();
            } while (umin2(v) == 0);
            __syncwarp();
            float mm = fmaxf(f32(v.x), __shfl_xor_sync(0xffffffffu, f32(v.x), 1));
            mm = fmaxf(mm, __shfl_xor_sync(0xffffffffu, mm, 2));
            float ll = f32(v.y) * exp_neg(f32(v.x) - mm);
            ll += __shfl_xor_sync(0xffffffffu, ll, 1);
            ll += __shfl_xor_sync(0xffffffffu, ll, 2);
            if (lane == 0) ml[8] = exp_neg(m - mm) / ll;
            bar_arrive(B_F, N_CX);
            fence_gpu();
            st_zero4(sc->x0 + cta * DH + lane * 4);
            if (lane < 16) st_zero4(sc->x0 + cta * DH + 128 + lane * 4);
        }
        {
            bar_sync(B_LATE, 64);
            const int j = lane < 24 ? lane : 0;
            const float* in = sc->x1 + cta * SPLIT * OROWS + 2 * j;
            uint2 v[SPLIT];
            unsigned spins = 0;
            do {
#pragma unroll
                for (int s = 0; s < SPLIT; s++) v[s] = ld_x2(in + s * OROWS);
                if (++spins > POLL_LIMIT) __trap();
            } while (min(min(umin2(v[0]), umin2(v[1])), min(umin2(v[2]), umin2(v[3]))) == 0);
            if (lane < 24)
                reinterpret_cast<uint32_t*>(smem + SM_O)[(j >> 3) * 8 + (j & 3) * 2 + ((j >> 2) & 1)] =
                    pack_bf16(sum4(f32(v[0].x), f32(v[1].x), f32(v[2].x), f32(v[3].x)), sum4(f32(v[0].y), f32(v[1].y), f32(v[2].y), f32(v[3].y)));
            bar_arrive(B_O, N_CX);
        }
        return;
    }

    if (warp == W_RED) {
        float* p = sc->x2 + cta * NCTA * 8 + lane * 4;
        st_zero4(sc->x1 + cta * SPLIT * OROWS + lane * 4);
        if (lane < 16) st_zero4(sc->x1 + cta * SPLIT * OROWS + 128 + lane * 4);
        if (lane < 2 * SPLIT) st_zero4(sc->xm + cta * SPLIT * 8 + lane * 4);
        if (cta < NRED) {
#pragma unroll
            for (int i = 0; i < 8; i++) st_zero4(p + i * 128);
        }
        __syncwarp();
        if (lane == 0) {
            fence_gpu();
            count(&sc->cleared);
        }
        if (cta >= NRED) return;
        __nv_bfloat16* po = out + cta * 8 + (lane & 1) * 4 + (lane >> 3);
        bar_sync(B_Y, N_CX);
        uint4 v[8];
#pragma unroll
        for (int i = 0; i < 8; i++) v[i] = ld_x4(p + i * 128);
        unsigned spins = 0;
        while (!__all_sync(0xffffffffu, min(min(min(umin4(v[0]), umin4(v[1])), min(umin4(v[2]), umin4(v[3]))),
                                            min(min(umin4(v[4]), umin4(v[5])), min(umin4(v[6]), umin4(v[7])))) != 0)) {
#pragma unroll
            for (int i = 0; i < 8; i++) if (umin4(v[i]) == 0) v[i] = ld_x4(p + i * 128);
            if (++spins > POLL_LIMIT) __trap();
        }
        const float s0 = sum4(f32(v[0].x), f32(v[1].x), f32(v[2].x), f32(v[3].x)) + sum4(f32(v[4].x), f32(v[5].x), f32(v[6].x), f32(v[7].x));
        const float s1 = sum4(f32(v[0].y), f32(v[1].y), f32(v[2].y), f32(v[3].y)) + sum4(f32(v[4].y), f32(v[5].y), f32(v[6].y), f32(v[7].y));
        const float s2 = sum4(f32(v[0].z), f32(v[1].z), f32(v[2].z), f32(v[3].z)) + sum4(f32(v[4].z), f32(v[5].z), f32(v[6].z), f32(v[7].z));
        const float s3 = sum4(f32(v[0].w), f32(v[1].w), f32(v[2].w), f32(v[3].w)) + sum4(f32(v[4].w), f32(v[5].w), f32(v[6].w), f32(v[7].w));
        const bool up = lane & 16, up2 = lane & 8;
        const float a0 = (up ? s2 : s0) + __shfl_xor_sync(0xffffffffu, up ? s0 : s2, 16);
        const float a1 = (up ? s3 : s1) + __shfl_xor_sync(0xffffffffu, up ? s1 : s3, 16);
        float b = (up2 ? a1 : a0) + __shfl_xor_sync(0xffffffffu, up2 ? a0 : a1, 8);
        b += __shfl_xor_sync(0xffffffffu, b, 4);
        b += __shfl_xor_sync(0xffffffffu, b, 2);
        if ((lane & 6) == 0) *po = __float2bfloat16_rn(b);
        if (cta == 0 && lane < 2) asm volatile("st.relaxed.gpu.global.b32 [%0], %1;" :: "l"(&sc->landed + 32 * lane), "r"(0) : "memory");
        return;
    }

    const int cw = warp - 1;
    const bool diag = (t == (g >> 1));
    const uint32_t sel0 = diag ? ((g & 1) ? 0x1044u : 0x4410u) : 0x4444u;
    const uint32_t sel1 = diag ? ((g & 1) ? 0x3244u : 0x4432u) : 0x4444u;
    uint32_t offk[4], offv[4];
    {
        const int mi = lane >> 3, rr = lane & 7;
#pragma unroll
        for (int j = 0; j < 4; j++) {
            offk[j] = cw * GRP + (rr + 8 * (mi & 1)) * ROWB + ((2 * j + (mi >> 1) + rr) & 7) * 16;
            offv[j] = cw * GRP + (rr + 8 * (mi >> 1)) * ROWB + ((2 * j + (mi & 1) + rr) & 7) * 16;
        }
    }
    float* red = reinterpret_cast<float*>(smem + SM_RED);
    uint32_t* pw = reinterpret_cast<uint32_t*>(smem + SM_P) + cw * (NTILE * 8);
    auto release = [&](int s) { __syncwarp(); if (lane == 0) mbar_arrive(empty + 8 * s); };

    float acc[12][4];
    {
        const int nq = cw < 2 ? 3 : 2;
        uint32_t xw[3];
#pragma unroll
        for (int i = 0; i < 3; i++) {
            xw[i] = 0;
            if (i < nq) {
                const unsigned short* xs = reinterpret_cast<const unsigned short*>(x) + r * XROWS + (cw + 4 * i) * 16 + g;
                xw[i] = (uint32_t)__ldg(xs) | ((uint32_t)__ldg(xs + 8) << 16);
            }
        }
#pragma unroll
        for (int i = 0; i < 12; i++) { acc[i][0] = acc[i][1] = acc[i][2] = acc[i][3] = 0.f; }
#pragma unroll 1
        for (int i = 0; i < 3; i++) {
            const uint32_t w = i == 0 ? xw[0] : (i == 1 ? xw[1] : xw[2]);
            wait_item(full, i);
            if (i < nq) rowsum_group(acc, ring + i * SLOT, offv, __byte_perm(w, 0, sel0), __byte_perm(w, 0, sel1));
            release(i);
        }
        rowsum_finish(acc, red + cw * DH, lane);
        bar_sync(B_CONS, NCW * 32);
        if (lane < 12) {
            const float4* r4 = reinterpret_cast<const float4*>(red) + cw * 12 + lane;
            const float4 a = r4[0], b = r4[DH / 4], c = r4[2 * DH / 4], d = r4[3 * DH / 4];
            st_x4(sc->x0 + cta * DH + cw * OROWS + lane * 4,
                  make_float4(sum4(a.x, b.x, c.x, d.x), sum4(a.y, b.y, c.y, d.y), sum4(a.z, b.z, c.z, d.z), sum4(a.w, b.w, c.w, d.w)));
        }
        bar_sync(B_Q, N_CX);
    }

    float mx = -INFINITY;
    {
        const uint32_t* qw = reinterpret_cast<const uint32_t*>(smem + SM_Q);
        uint32_t qb[3][8];
#pragma unroll
        for (int s = 0; s < 3; s++)
#pragma unroll
            for (int u = 0; u < 8; u++) qb[s][u] = qw[32 * s + 4 * ((u + g) & 7) + t];
        const float scale = 0.07216878364870322f;
#pragma unroll 1
        for (int i = 0; i < NTILE; i++) {
            const int slot = (unsigned)(IT_K + i) % NSLOT;
            wait_item(full, IT_K + i);
            const uint32_t sa = ring + slot * SLOT;
            float c[3][4];
#pragma unroll
            for (int s = 0; s < 3; s++) {
                uint32_t a[4][4];
                c[s][0] = c[s][1] = c[s][2] = c[s][3] = 0.f;
#pragma unroll
                for (int j = 0; j < 4; j++) ldsm4(a[j], sa + offk[j] + s * 128);
#pragma unroll
                for (int j = 0; j < 4; j++) mma16816(c[s], a[j], qb[s][2 * j], qb[s][2 * j + 1]);
            }
            release(slot);
            const bool odd = g & 1;
            float lo = odd ? (c[0][1] + c[1][1]) + c[2][1] : (c[0][0] + c[1][0]) + c[2][0];
            float hi = odd ? (c[0][3] + c[1][3]) + c[2][3] : (c[0][2] + c[1][2]) + c[2][2];
            lo = bf16r(bf16r(lo) * scale);
            hi = bf16r(bf16r(hi) * scale);
            if (diag) {
                mx = fmaxf(mx, fmaxf(lo, hi));
                pw[i * 8 + g] = pack_bf16(lo, hi);
            }
        }
    }
    {
#pragma unroll
        for (int o = 16; o > 0; o >>= 1) mx = fmaxf(mx, __shfl_xor_sync(0xffffffffu, mx, o));
        if (lane == 0) ml[cw] = mx;
        bar_sync(B_CONS, NCW * 32);
        mx = fmaxf(fmaxf(ml[0], ml[1]), fmaxf(ml[2], ml[3]));
        float lsum = 0.f;
#pragma unroll
        for (int i = 0; i < NTILE * 8 / 32; i++) {
            const uint32_t w = pw[i * 32 + lane];
            const float e0 = exp_neg(f32(w << 16) - mx), e1 = exp_neg(f32(w & 0xffff0000u) - mx);
            lsum += e0 + e1;
            pw[i * 32 + lane] = pack_bf16(e0, e1);
        }
#pragma unroll
        for (int o = 16; o > 0; o >>= 1) lsum += __shfl_xor_sync(0xffffffffu, lsum, o);
        if (lane == 0) ml[4 + cw] = lsum;
        __syncwarp();
        bar_arrive(B_L, N_CX);
    }
#pragma unroll
    for (int i = 0; i < 12; i++) { acc[i][0] = acc[i][1] = acc[i][2] = acc[i][3] = 0.f; }
#pragma unroll 1
    for (int i = 0; i < NTILE; i++) {
        const int slot = (unsigned)(IT_V + i) % NSLOT;
        const uint32_t w = pw[i * 8 + g];
        wait_item(full, IT_V + i);
        rowsum_group(acc, ring + slot * SLOT, offv, __byte_perm(w, 0, sel0), __byte_perm(w, 0, sel1));
        release(slot);
    }
    rowsum_finish(acc, red + cw * DH, lane);
    bar_sync(B_F, N_CX);
    if (lane < 12) {
        const float f = ml[8];
        const float4* r4 = reinterpret_cast<const float4*>(red) + cw * 12 + lane;
        const float4 a = r4[0], b = r4[DH / 4], c = r4[2 * DH / 4], d = r4[3 * DH / 4];
        st_x4(sc->x1 + ((h * SPLIT + cw) * SPLIT + r) * OROWS + lane * 4,
              make_float4(sum4(a.x, b.x, c.x, d.x) * f, sum4(a.y, b.y, c.y, d.y) * f, sum4(a.z, b.z, c.z, d.z) * f, sum4(a.w, b.w, c.w, d.w) * f));
    }
    __syncwarp();
    {
        uint32_t offw = ring + ((lane & 7) + 8 * (lane >> 4)) * 128 + (((2 * cw + ((lane >> 3) & 1)) ^ (lane & 7)) * 16);
        float* dst = sc->x2 + ((8 * (t >> 1) + 2 * cw + (t & 1)) * NCTA + cta) * 8 + g;
        asm volatile("" : "+r"(offw), "+l"(dst));
        constexpr int S0 = IT_O % NSLOT, S1 = (IT_O + 1) % NSLOT, S2 = (IT_O + 2) % NSLOT;
        uint32_t a0[10][4], a1[10][4], a2[10][4];
        wait_item(full, IT_O);
#pragma unroll
        for (int b = 0; b < 10; b++) ldsm4t(a0[b], offw + b * 2048 + S0 * SLOT);
        wait_item(full, IT_O + 1);
#pragma unroll
        for (int b = 0; b < 10; b++) ldsm4t(a1[b], offw + b * 2048 + S1 * SLOT);
        bar_sync(B_O, N_CX);
        uint2 ob[3];
#pragma unroll
        for (int ks = 0; ks < 3; ks++) ob[ks] = reinterpret_cast<const uint2*>(smem + SM_O)[ks * 4 + t];
        const bool early = __all_sync(0xffffffffu, mbar_test(full + 8 * S2, ((IT_O + 2) / NSLOT) & 1));
        float y[10][4];
#pragma unroll
        for (int b = 0; b < 10; b++) { y[b][0] = y[b][1] = y[b][2] = y[b][3] = 0.f; }
        if (early) {
#pragma unroll
            for (int b = 0; b < 10; b++) ldsm4t(a2[b], offw + b * 2048 + S2 * SLOT);
        }
#pragma unroll
        for (int b = 0; b < 10; b++) mma16816(y[b], a0[b], ob[0].x, ob[0].y);
#pragma unroll
        for (int b = 0; b < 10; b++) mma16816(y[b], a1[b], ob[1].x, ob[1].y);
        if (!early) {
            wait_item(full, IT_O + 2);
#pragma unroll
            for (int b = 0; b < 10; b++) ldsm4t(a2[b], offw + b * 2048 + S2 * SLOT);
        }
#pragma unroll
        for (int b = 0; b < 10; b++) mma16816(y[b], a2[b], ob[2].x, ob[2].y);
#pragma unroll
        for (int i = 0; i < 5; i++) {
            const float v = (t & 2) ? ((t & 1) ? y[2 * i + 1][2] : y[2 * i + 1][0]) : ((t & 1) ? y[2 * i][2] : y[2 * i][0]);
            st_x(dst + i * 16 * NCTA * 8, v);
        }
        if (cta < NRED) bar_arrive(B_Y, N_CX);
    }
}

typedef CUresult (*EncodeTiledFn)(CUtensorMap*, CUtensorMapDataType, cuuint32_t, void*, const cuuint64_t*, const cuuint64_t*,
                                  const cuuint32_t*, const cuuint32_t*, CUtensorMapInterleave, CUtensorMapSwizzle,
                                  CUtensorMapL2promotion, CUtensorMapFloatOOBfill);

}

extern "C" void kernel_launch(void* const* d_in, const int* in_sizes, int n_in, void* d_out, int out_size) {
    (void)in_sizes; (void)n_in; (void)out_size;
    using namespace gqa;
    static EncodeTiledFn encode = nullptr;
    static Scratch* scratch = nullptr;
    if (!encode) {
        cudaGetSymbolAddress((void**)&scratch, g_scratch);
        void* fn = nullptr;
        cudaDriverEntryPointQueryResult qr;
        cudaGetDriverEntryPoint("cuTensorMapEncodeTiled", &fn, cudaEnableDefault, &qr);
        encode = (EncodeTiledFn)fn;
        cudaFuncSetAttribute(gqa_decode_kernel, cudaFuncAttributeMaxDynamicSharedMemorySize, SM_TOTAL);
    }
    CUtensorMap tm_wq, tm_wo;
    {
        cuuint64_t dims[2] = {QCOLS, D_MODEL}, strides[1] = {QCOLS * 2};
        cuuint32_t box[2] = {DH, 32}, es[2] = {1, 1};
        encode(&tm_wq, CU_TENSOR_MAP_DATA_TYPE_BFLOAT16, 2, d_in[3], dims, strides, box, es, CU_TENSOR_MAP_INTERLEAVE_NONE,
               CU_TENSOR_MAP_SWIZZLE_NONE, CU_TENSOR_MAP_L2_PROMOTION_NONE, CU_TENSOR_MAP_FLOAT_OOB_FILL_NONE);
    }
    {
        cuuint64_t dims[3] = {64, QCOLS, D_MODEL / 64}, strides[2] = {D_MODEL * 2, 128};
        cuuint32_t box[3] = {64, 16, D_MODEL / 64}, es[3] = {1, 1, 1};
        encode(&tm_wo, CU_TENSOR_MAP_DATA_TYPE_BFLOAT16, 3, d_in[4], dims, strides, box, es, CU_TENSOR_MAP_INTERLEAVE_NONE,
               CU_TENSOR_MAP_SWIZZLE_128B, CU_TENSOR_MAP_L2_PROMOTION_NONE, CU_TENSOR_MAP_FLOAT_OOB_FILL_NONE);
    }
    gqa_decode_kernel<<<NCTA, NTHREADS, SM_TOTAL>>>((const __nv_bfloat16*)d_in[1], (const __nv_bfloat16*)d_in[2],
                                                    (const __nv_bfloat16*)d_in[0], (__nv_bfloat16*)d_out, scratch, tm_wq, tm_wo);
}
```

```cpp
#include <cuda_runtime.h>
#include <cuda.h>
#include <cuda_bf16.h>
#include <stdint.h>

namespace gqa {

constexpr int D_MODEL = 640;
constexpr int NH      = 32;
constexpr int SK      = 8192;
constexpr int DH      = 192;
constexpr int QCOLS   = NH * DH;
constexpr int SPLIT   = 4;
constexpr int NCTA    = NH * SPLIT;
constexpr int NCW     = 4;
constexpr int W_XCHG = NCW + 1, W_COUNT = NCW + 2, W_CLEAR = NCW + 3;
constexpr int NTHREADS = (NCW + 4) * 32;
constexpr int TOK_CTA = SK / SPLIT;
constexpr int NTILE   = TOK_CTA / 64;
constexpr int ROWB    = DH * 2;
constexpr int GRP     = 16 * ROWB;
constexpr int SLOT    = NCW * GRP;
constexpr int NSLOT   = 8;
constexpr int XROWS   = D_MODEL / SPLIT;
constexpr int OROWS   = DH / SPLIT;
constexpr int WOB     = 16 * D_MODEL * 2;
constexpr int NACC    = D_MODEL / 8;
constexpr int ACC_PITCH = 512;
constexpr int IT_K = 3, IT_V = IT_K + NTILE, IT_O = IT_V + NTILE, IT_END = IT_O + 3;

constexpr int WIN_HEAD = 3, HEAD_UNTIL = NSLOT + IT_K;
constexpr int PACE_FROM = 48, PACE_KV = 640, PACE_WO = 384, PACE_MIN = 32;

constexpr int SM_RING = 0;
constexpr int SM_BARS = SM_RING + NSLOT * SLOT;
constexpr int SM_P    = SM_BARS + 128;
constexpr int SM_RED  = SM_P + NCW * NTILE * 8 * 4;
constexpr int SM_ML   = SM_RED + NCW * DH * 4;
constexpr int SM_Q    = SM_ML + 64;
constexpr int SM_O    = SM_Q + DH * 2;
constexpr int SM_TOTAL = SM_O + 128;
constexpr int B_CONS = 1, B_Q = 2, B_L = 3, B_F = 4, B_LATE = 5, B_O = 6;
constexpr int N_CX = (NCW + 1) * 32;

constexpr unsigned MBAR_LIMIT = 1u << 19, POLL_LIMIT = 1u << 22;

struct Scratch {
    float x2[NACC * ACC_PITCH];
    float x0[NCTA * DH];
    float x1[NCTA * SPLIT * OROWS];
    float xm[NCTA * SPLIT * 8];
    unsigned landed;
    unsigned pad[31];
    unsigned cleared;
};
__device__ __align__(128) Scratch g_scratch;

__device__ __forceinline__ uint32_t smem_u32(const void* p) { return (uint32_t)__cvta_generic_to_shared(p); }

__device__ __forceinline__ void mbar_init(uint32_t bar, uint32_t cnt) {
    asm volatile("mbarrier.init.shared::cta.b64 [%0], %1;" :: "r"(bar), "r"(cnt) : "memory");
}
__device__ __forceinline__ void mbar_init_fence() { asm volatile("fence.mbarrier_init.release.cluster;" ::: "memory"); }
__device__ __forceinline__ void mbar_expect_tx(uint32_t bar, uint32_t bytes) {
    asm volatile("mbarrier.arrive.expect_tx.shared::cta.b64 _, [%0], %1;" :: "r"(bar), "r"(bytes) : "memory");
}
__device__ __forceinline__ void mbar_arrive(uint32_t bar) {
    asm volatile("mbarrier.arrive.shared::cta.b64 _, [%0];" :: "r"(bar) : "memory");
}
__device__ __forceinline__ bool mbar_try(uint32_t bar, uint32_t parity) {
    uint32_t ok;
    asm volatile("{\n.reg .pred p;\nmbarrier.try_wait.parity.shared::cta.b64 p, [%1], %2;\nselp.u32 %0, 1, 0, p;\n}"
                 : "=r"(ok) : "r"(bar), "r"(parity) : "memory");
    return ok;
}
__device__ __forceinline__ bool mbar_test(uint32_t bar, uint32_t parity) {
    uint32_t ok;
    asm volatile("{\n.reg .pred p;\nmbarrier.test_wait.parity.shared::cta.b64 p, [%1], %2;\nselp.u32 %0, 1, 0, p;\n}"
                 : "=r"(ok) : "r"(bar), "r"(parity) : "memory");
    return ok;
}
__device__ __forceinline__ void mbar_wait(uint32_t bar, uint32_t parity) {
    if (mbar_try(bar, parity)) return;
    unsigned spins = 0;
    while (!mbar_try(bar, parity)) if (++spins > MBAR_LIMIT) __trap();
}
__device__ __forceinline__ void wait_item(uint32_t full, unsigned it) { mbar_wait(full + 8 * (it % NSLOT), (it / NSLOT) & 1); }

constexpr uint64_t STREAM = 0x12F0000000000000ull;
__device__ __forceinline__ void bulk_load(uint32_t dst, const void* src, uint32_t bytes, uint32_t bar) {
    asm volatile("cp.async.bulk.shared::cluster.global.mbarrier::complete_tx::bytes.L2::cache_hint [%0], [%1], %2, [%3], %4;"
                 :: "r"(dst), "l"(src), "r"(bytes), "r"(bar), "l"(STREAM) : "memory");
}
__device__ __forceinline__ void tma_2d(uint32_t dst, const CUtensorMap* tm, int c0, int c1, uint32_t bar) {
    asm volatile("cp.async.bulk.tensor.2d.shared::cluster.global.mbarrier::complete_tx::bytes.L2::cache_hint [%0], [%1, {%3, %4}], [%2], %5;"
                 :: "r"(dst), "l"(tm), "r"(bar), "r"(c0), "r"(c1), "l"(STREAM) : "memory");
}
__device__ __forceinline__ void tma_3d(uint32_t dst, const CUtensorMap* tm, int c0, int c1, int c2, uint32_t bar) {
    asm volatile("cp.async.bulk.tensor.3d.shared::cluster.global.mbarrier::complete_tx::bytes.L2::cache_hint [%0], [%1, {%3, %4, %5}], [%2], %6;"
                 :: "r"(dst), "l"(tm), "r"(bar), "r"(c0), "r"(c1), "r"(c2), "l"(STREAM) : "memory");
}
__device__ __forceinline__ void ldsm4(uint32_t (&a)[4], uint32_t addr) {
    asm volatile("ldmatrix.sync.aligned.m8n8.x4.shared.b16 {%0,%1,%2,%3}, [%4];"
                 : "=r"(a[0]), "=r"(a[1]), "=r"(a[2]), "=r"(a[3]) : "r"(addr) : "memory");
}
__device__ __forceinline__ void ldsm4t(uint32_t (&a)[4], uint32_t addr) {
    asm volatile("ldmatrix.sync.aligned.m8n8.x4.trans.shared.b16 {%0,%1,%2,%3}, [%4];"
                 : "=r"(a[0]), "=r"(a[1]), "=r"(a[2]), "=r"(a[3]) : "r"(addr) : "memory");
}
__device__ __forceinline__ void mma16816(float (&c)[4], const uint32_t (&a)[4], uint32_t b0, uint32_t b1) {
    asm volatile("mma.sync.aligned.m16n8k16.row.col.f32.bf16.bf16.f32 {%0,%1,%2,%3}, {%4,%5,%6,%7}, {%8,%9}, {%0,%1,%2,%3};"
                 : "+f"(c[0]), "+f"(c[1]), "+f"(c[2]), "+f"(c[3])
                 : "r"(a[0]), "r"(a[1]), "r"(a[2]), "r"(a[3]), "r"(b0), "r"(b1));
}
__device__ __forceinline__ void bar_sync(int id, int n) { asm volatile("bar.sync %0, %1;" :: "r"(id), "r"(n) : "memory"); }
__device__ __forceinline__ void bar_arrive(int id, int n) { asm volatile("bar.arrive %0, %1;" :: "r"(id), "r"(n) : "memory"); }
__device__ __forceinline__ void fence_gpu() { asm volatile("fence.acq_rel.gpu;" ::: "memory"); }

__device__ __forceinline__ uint32_t enc(float v) { uint32_t u = __float_as_uint(v); return u ? u : 0x80000000u; }
__device__ __forceinline__ void st_x4(float* p, float4 v) {
    asm volatile("st.relaxed.gpu.global.v4.b32 [%0], {%1,%2,%3,%4};"
                 :: "l"(p), "r"(enc(v.x)), "r"(enc(v.y)), "r"(enc(v.z)), "r"(enc(v.w)) : "memory");
}
__device__ __forceinline__ void st_zero4(float* p) {
    asm volatile("st.relaxed.gpu.global.v4.b32 [%0], {%1,%1,%1,%1};" :: "l"(p), "r"(0) : "memory");
}
__device__ __forceinline__ uint32_t ld_x(const unsigned* p) {
    uint32_t v;
    asm volatile("ld.relaxed.gpu.global.b32 %0, [%1];" : "=r"(v) : "l"(p) : "memory");
    return v;
}
__device__ __forceinline__ uint2 ld_x2(const float* p) {
    uint2 v;
    asm volatile("ld.relaxed.gpu.global.v2.b32 {%0,%1}, [%2];" : "=r"(v.x), "=r"(v.y) : "l"(p) : "memory");
    return v;
}
__device__ __forceinline__ void count(unsigned* p) { asm volatile("red.relaxed.gpu.global.add.u32 [%0], 1;" :: "l"(p) : "memory"); }
__device__ __forceinline__ uint32_t umin2(uint2 v) { return min(v.x, v.y); }
__device__ __forceinline__ float f32(uint32_t u) { return __uint_as_float(u); }
__device__ __forceinline__ float sum4(float a, float b, float c, float d) { return (a + b) + (c + d); }

__device__ __forceinline__ float bf16r(float v) { return __bfloat162float(__float2bfloat16_rn(v)); }
__device__ __forceinline__ uint32_t pack_bf16(float lo, float hi) {
    __nv_bfloat162 h = __floats2bfloat162_rn(lo, hi);
    return *reinterpret_cast<uint32_t*>(&h);
}
__device__ __forceinline__ float exp_neg(float v) {
    float r;
    asm("ex2.approx.ftz.f32 %0, %1;" : "=f"(r) : "f"(v * 1.4426950408889634f));
    return r;
}

__device__ __forceinline__ void rowsum_group(float (&acc)[12][4], uint32_t slot, const uint32_t (&off)[4], uint32_t b0, uint32_t b1) {
#pragma unroll
    for (int s = 0; s < 3; s++) {
        uint32_t a[4][4];
#pragma unroll
        for (int j = 0; j < 4; j++) ldsm4t(a[j], slot + off[j] + s * 128);
#pragma unroll
        for (int j = 0; j < 4; j++) mma16816(acc[s * 4 + j], a[j], b0, b1);
    }
}
__device__ __forceinline__ void rowsum_finish(const float (&acc)[12][4], float* red, int lane) {
    const int g = lane >> 2, t = lane & 3;
    const int from = (lane & ~3) | ((t + 3) & 3);
#pragma unroll
    for (int s = 0; s < 3; s++) {
        float val[8];
#pragma unroll
        for (int j = 0; j < 4; j++) {
            val[2 * j]     = acc[s * 4 + j][0] + acc[s * 4 + ((j + 3) & 3)][3];
            val[2 * j + 1] = acc[s * 4 + j][1] + acc[s * 4 + j][2];
        }
        float nw[4];
#pragma unroll
        for (int v = 0; v < 4; v++) nw[v] = val[v] + __shfl_xor_sync(0xffffffffu, val[v + 4], 2);
#pragma unroll
        for (int v = 0; v < 2; v++) red[64 * s + 8 * (2 * t + v) + g] = nw[v] + __shfl_sync(0xffffffffu, nw[v + 2], from);
    }
}
__device__ __forceinline__ void issue_wq(uint32_t ring, uint32_t full, const CUtensorMap* tm, int h, int r, int i) {
    mbar_expect_tx(full + 8 * i, i < 2 ? SLOT : SLOT / 2);
    tma_2d(ring + i * SLOT, tm, h * DH, r * XROWS + i * 64, full + 8 * i);
    if (i < 2) tma_2d(ring + i * SLOT + SLOT / 2, tm, h * DH, r * XROWS + i * 64 + 32, full + 8 * i);
}

__global__ void __launch_bounds__(NTHREADS, 1)
gqa_decode_kernel(const __nv_bfloat16* __restrict__ kc, const __nv_bfloat16* __restrict__ vc,
                  const __nv_bfloat16* __restrict__ x, __nv_bfloat16* __restrict__ out, Scratch* __restrict__ sc,
                  const __grid_constant__ CUtensorMap tm_wq, const __grid_constant__ CUtensorMap tm_wo) {
    extern __shared__ __align__(1024) unsigned char smem[];
    const int tid = threadIdx.x, warp = tid >> 5, lane = tid & 31;
    const int cta = blockIdx.x, h = cta >> 2, r = cta & 3;
    const uint32_t ring = smem_u32(smem) + SM_RING;
    const uint32_t full = smem_u32(smem) + SM_BARS, empty = full + NSLOT * 8;
    const unsigned char* kp = reinterpret_cast<const unsigned char*>(kc) + (size_t)cta * (TOK_CTA * ROWB);

    if (tid == 0) {
        mbar_init(full + 8 * IT_K, 1);
        mbar_init_fence();
        mbar_expect_tx(full + 8 * IT_K, SLOT);
        bulk_load(ring + IT_K * SLOT, kp, SLOT, full + 8 * IT_K);
#pragma unroll
        for (int i = 0; i < NSLOT; i++) if (i != IT_K) mbar_init(full + 8 * i, 1);
        mbar_init_fence();
        issue_wq(ring, full, &tm_wq, h, r, 0);
        issue_wq(ring, full, &tm_wq, h, r, 1);
#pragma unroll
        for (int i = 0; i < NSLOT; i++) mbar_init(empty + 8 * i, NCW + 1);
    }
    __syncthreads();
    const int g = lane >> 2, t = lane & 3;
    float* ml = reinterpret_cast<float*>(smem + SM_ML);

    if (warp == 0) {
        if (lane == 0) {
            const unsigned char* vp = reinterpret_cast<const unsigned char*>(vc) + (size_t)cta * (TOK_CTA * ROWB);
            asm volatile("prefetch.tensormap [%0];" :: "l"(&tm_wo) : "memory");
            wait_item(full, IT_K);
            issue_wq(ring, full, &tm_wq, h, r, 2);
            int landed = 0;
#pragma unroll 1
            for (int it = IT_K + 1; it < IT_END; it++) {
                const int s = (unsigned)it % NSLOT, n = it - IT_K;
                if (n >= PACE_FROM) {
                    const int need = it < IT_O ? NCTA * n + cta - PACE_KV
                                               : min(NCTA * n + cta - PACE_WO, NCTA * 2 * NTILE - PACE_MIN);
                    unsigned spins = 0;
                    while (landed < need) {
                        landed = ld_x(&sc->landed);
                        if (++spins > POLL_LIMIT) __trap();
                    }
                }
                if (it < HEAD_UNTIL) wait_item(full, it - WIN_HEAD <= IT_K ? it - WIN_HEAD - 1 : it - WIN_HEAD);
                if (it >= NSLOT) mbar_wait(empty + 8 * s, ((it / NSLOT) & 1) ^ 1);
                if (it < IT_O) {
                    mbar_expect_tx(full + 8 * s, SLOT);
                    bulk_load(ring + s * SLOT, it < IT_V ? kp + (size_t)n * SLOT : vp + (size_t)(it - IT_V) * SLOT, SLOT, full + 8 * s);
                } else {
                    mbar_expect_tx(full + 8 * s, WOB);
                    tma_3d(ring + s * SLOT, &tm_wo, 0, cta * OROWS + (it - IT_O) * 16, 0, full + 8 * s);
                }
            }
        }
        return;
    }

    if (warp == W_COUNT) {
        if (lane < IT_K) mbar_arrive(empty + 8 * lane);
#pragma unroll 1
        for (int it = IT_K; it < IT_O; it++) {
            wait_item(full, it);
            __syncwarp();
            if (lane == 0) {
                count(&sc->landed);
                mbar_arrive(empty + 8 * ((unsigned)it % NSLOT));
            }
            if (it == IT_O - 2) bar_arrive(B_LATE, 64);
        }
        return;
    }

    if (warp == W_XCHG) {
        {
            const float* in = sc->x0 + h * SPLIT * DH + 2 * lane;
            uint2 v[SPLIT][3];
            unsigned spins = 0, lo;
            do {
                lo = 0xffffffffu;
#pragma unroll
                for (int s = 0; s < SPLIT; s++)
#pragma unroll
                    for (int i = 0; i < 3; i++) v[s][i] = ld_x2(in + s * DH + i * 64);
#pragma unroll
                for (int s = 0; s < SPLIT; s++)
#pragma unroll
                    for (int i = 0; i < 3; i++) lo = min(lo, umin2(v[s][i]));
                if (++spins > POLL_LIMIT) __trap();
            } while (lo == 0);
            uint32_t* qw = reinterpret_cast<uint32_t*>(smem + SM_Q);
#pragma unroll
            for (int i = 0; i < 3; i++)
                qw[i * 32 + lane] = pack_bf16(sum4(f32(v[0][i].x), f32(v[1][i].x), f32(v[2][i].x), f32(v[3][i].x)),
                                              sum4(f32(v[0][i].y), f32(v[1][i].y), f32(v[2][i].y), f32(v[3][i].y)));
            bar_arrive(B_Q, N_CX);
        }
        {
            unsigned spins = 0;
            while (ld_x(&sc->cleared) < NCTA) if (++spins > POLL_LIMIT) __trap();
            fence_gpu();
        }
        {
            bar_sync(B_L, N_CX);
            const float m = fmaxf(fmaxf(ml[0], ml[1]), fmaxf(ml[2], ml[3]));
            const float l = sum4(ml[4], ml[5], ml[6], ml[7]);
            if (lane < 2 * SPLIT) st_x4(sc->xm + ((h * SPLIT + (lane >> 1)) * SPLIT + r) * 8 + (lane & 1) * 4, make_float4(m, l, m, l));
            const float* in = sc->xm + (cta * SPLIT + (lane & 3)) * 8;
            uint2 v;
            unsigned spins = 0;
            do {
                v = ld_x2(in);
                if (++spins > POLL_LIMIT) __trap();
            } while (umin2(v) == 0);
            __syncwarp();
            float mm = fmaxf(f32(v.x), __shfl_xor_sync(0xffffffffu, f32(v.x), 1));
            mm = fmaxf(mm, __shfl_xor_sync(0xffffffffu, mm, 2));
            float ll = f32(v.y) * exp_neg(f32(v.x) - mm);
            ll += __shfl_xor_sync(0xffffffffu, ll, 1);
            ll += __shfl_xor_sync(0xffffffffu, ll, 2);
            if (lane == 0) ml[8] = exp_neg(m - mm) / ll;
            bar_arrive(B_F, N_CX);
            fence_gpu();
            st_zero4(sc->x0 + cta * DH + lane * 4);
            if (lane < 16) st_zero4(sc->x0 + cta * DH + 128 + lane * 4);
        }
        {
            bar_sync(B_LATE, 64);
            const int j = lane < 24 ? lane : 0;
            const float* in = sc->x1 + cta * SPLIT * OROWS + 2 * j;
            uint2 v[SPLIT];
            unsigned spins = 0;
            do {
#pragma unroll
                for (int s = 0; s < SPLIT; s++) v[s] = ld_x2(in + s * OROWS);
                if (++spins > POLL_LIMIT) __trap();
            } while (min(min(umin2(v[0]), umin2(v[1])), min(umin2(v[2]), umin2(v[3]))) == 0);
            if (lane < 24)
                reinterpret_cast<uint32_t*>(smem + SM_O)[(j >> 3) * 8 + (j & 3) * 2 + ((j >> 2) & 1)] =
                    pack_bf16(sum4(f32(v[0].x), f32(v[1].x), f32(v[2].x), f32(v[3].x)), sum4(f32(v[0].y), f32(v[1].y), f32(v[2].y), f32(v[3].y)));
            bar_arrive(B_O, N_CX);
        }
        return;
    }

    if (warp == W_CLEAR) {
        st_zero4(sc->x1 + cta * SPLIT * OROWS + lane * 4);
        if (lane < 16) st_zero4(sc->x1 + cta * SPLIT * OROWS + 128 + lane * 4);
        if (lane < 2 * SPLIT) st_zero4(sc->xm + cta * SPLIT * 8 + lane * 4);
        if (cta < NACC && lane < 4) st_zero4(sc->x2 + cta * ACC_PITCH + lane * 4);
        __syncwarp();
        if (lane == 0) {
            fence_gpu();
            count(&sc->cleared);
        }
        return;
    }

    const int cw = warp - 1;
    const bool diag = (t == (g >> 1));
    const uint32_t sel0 = diag ? ((g & 1) ? 0x1044u : 0x4410u) : 0x4444u;
    const uint32_t sel1 = diag ? ((g & 1) ? 0x3244u : 0x4432u) : 0x4444u;
    uint32_t offk[4], offv[4];
    {
        const int mi = lane >> 3, rr = lane & 7;
#pragma unroll
        for (int j = 0; j < 4; j++) {
            offk[j] = cw * GRP + (rr + 8 * (mi & 1)) * ROWB + ((2 * j + (mi >> 1) + rr) & 7) * 16;
            offv[j] = cw * GRP + (rr + 8 * (mi >> 1)) * ROWB + ((2 * j + (mi & 1) + rr) & 7) * 16;
        }
    }
    float* red = reinterpret_cast<float*>(smem + SM_RED);
    uint32_t* pw = reinterpret_cast<uint32_t*>(smem + SM_P) + cw * (NTILE * 8);
    auto release = [&](int s) { __syncwarp(); if (lane == 0) mbar_arrive(empty + 8 * s); };

    float acc[12][4];
    {
        const int nq = cw < 2 ? 3 : 2;
        uint32_t xw[3];
#pragma unroll
        for (int i = 0; i < 3; i++) {
            xw[i] = 0;
            if (i < nq) {
                const unsigned short* xs = reinterpret_cast<const unsigned short*>(x) + r * XROWS + (cw + 4 * i) * 16 + g;
                xw[i] = (uint32_t)__ldg(xs) | ((uint32_t)__ldg(xs + 8) << 16);
            }
        }
#pragma unroll
        for (int i = 0; i < 12; i++) { acc[i][0] = acc[i][1] = acc[i][2] = acc[i][3] = 0.f; }
#pragma unroll 1
        for (int i = 0; i < 3; i++) {
            const uint32_t w = i == 0 ? xw[0] : (i == 1 ? xw[1] : xw[2]);
            wait_item(full, i);
            if (i < nq) rowsum_group(acc, ring + i * SLOT, offv, __byte_perm(w, 0, sel0), __byte_perm(w, 0, sel1));
            release(i);
        }
        rowsum_finish(acc, red + cw * DH, lane);
        bar_sync(B_CONS, NCW * 32);
        if (lane < 12) {
            const float4* r4 = reinterpret_cast<const float4*>(red) + cw * 12 + lane;
            const float4 a = r4[0], b = r4[DH / 4], c = r4[2 * DH / 4], d = r4[3 * DH / 4];
            st_x4(sc->x0 + cta * DH + cw * OROWS + lane * 4,
                  make_float4(sum4(a.x, b.x, c.x, d.x), sum4(a.y, b.y, c.y, d.y), sum4(a.z, b.z, c.z, d.z), sum4(a.w, b.w, c.w, d.w)));
        }
        bar_sync(B_Q, N_CX);
    }

    float mx = -INFINITY;
    {
        const uint32_t* qw = reinterpret_cast<const uint32_t*>(smem + SM_Q);
        uint32_t qb[3][8];
#pragma unroll
        for (int s = 0; s < 3; s++)
#pragma unroll
            for (int u = 0; u < 8; u++) qb[s][u] = qw[32 * s + 4 * ((u + g) & 7) + t];
        const float scale = 0.07216878364870322f;
#pragma unroll 1
        for (int i = 0; i < NTILE; i++) {
            const int slot = (unsigned)(IT_K + i) % NSLOT;
            wait_item(full, IT_K + i);
            const uint32_t sa = ring + slot * SLOT;
            float c[3][4];
#pragma unroll
            for (int s = 0; s < 3; s++) {
                uint32_t a[4][4];
                c[s][0] = c[s][1] = c[s][2] = c[s][3] = 0.f;
#pragma unroll
                for (int j = 0; j < 4; j++) ldsm4(a[j], sa + offk[j] + s * 128);
#pragma unroll
                for (int j = 0; j < 4; j++) mma16816(c[s], a[j], qb[s][2 * j], qb[s][2 * j + 1]);
            }
            release(slot);
            const bool odd = g & 1;
            float lo = odd ? (c[0][1] + c[1][1]) + c[2][1] : (c[0][0] + c[1][0]) + c[2][0];
            float hi = odd ? (c[0][3] + c[1][3]) + c[2][3] : (c[0][2] + c[1][2]) + c[2][2];
            lo = bf16r(bf16r(lo) * scale);
            hi = bf16r(bf16r(hi) * scale);
            if (diag) {
                mx = fmaxf(mx, fmaxf(lo, hi));
                pw[i * 8 + g] = pack_bf16(lo, hi);
            }
        }
    }
    {
#pragma unroll
        for (int o = 16; o > 0; o >>= 1) mx = fmaxf(mx, __shfl_xor_sync(0xffffffffu, mx, o));
        if (lane == 0) ml[cw] = mx;
        bar_sync(B_CONS, NCW * 32);
        mx = fmaxf(fmaxf(ml[0], ml[1]), fmaxf(ml[2], ml[3]));
        float lsum = 0.f;
#pragma unroll
        for (int i = 0; i < NTILE * 8 / 32; i++) {
            const uint32_t w = pw[i * 32 + lane];
            const float e0 = exp_neg(f32(w << 16) - mx), e1 = exp_neg(f32(w & 0xffff0000u) - mx);
            lsum += e0 + e1;
            pw[i * 32 + lane] = pack_bf16(e0, e1);
        }
#pragma unroll
        for (int o = 16; o > 0; o >>= 1) lsum += __shfl_xor_sync(0xffffffffu, lsum, o);
        if (lane == 0) ml[4 + cw] = lsum;
        __syncwarp();
        bar_arrive(B_L, N_CX);
    }
#pragma unroll
    for (int i = 0; i < 12; i++) { acc[i][0] = acc[i][1] = acc[i][2] = acc[i][3] = 0.f; }
#pragma unroll 1
    for (int i = 0; i < NTILE; i++) {
        const int slot = (unsigned)(IT_V + i) % NSLOT;
        const uint32_t w = pw[i * 8 + g];
        wait_item(full, IT_V + i);
        rowsum_group(acc, ring + slot * SLOT, offv, __byte_perm(w, 0, sel0), __byte_perm(w, 0, sel1));
        release(slot);
    }
    rowsum_finish(acc, red + cw * DH, lane);
    bar_sync(B_F, N_CX);
    if (lane < 12) {
        const float f = ml[8];
        const float4* r4 = reinterpret_cast<const float4*>(red) + cw * 12 + lane;
        const float4 a = r4[0], b = r4[DH / 4], c = r4[2 * DH / 4], d = r4[3 * DH / 4];
        st_x4(sc->x1 + ((h * SPLIT + cw) * SPLIT + r) * OROWS + lane * 4,
              make_float4(sum4(a.x, b.x, c.x, d.x) * f, sum4(a.y, b.y, c.y, d.y) * f, sum4(a.z, b.z, c.z, d.z) * f, sum4(a.w, b.w, c.w, d.w) * f));
    }
    __syncwarp();
    {
        uint32_t offw = ring + ((lane & 7) + 8 * (lane >> 4)) * 128 + (((2 * cw + ((lane >> 3) & 1)) ^ (lane & 7)) * 16);
        const int u0 = 8 * (t >> 1) + 2 * cw + (t & 1);
        float* dst = sc->x2 + u0 * ACC_PITCH + 2 * g;
        __nv_bfloat16* po = out + u0 * 8 + g;
        asm volatile("" : "+r"(offw), "+l"(dst), "+l"(po));
        constexpr int S0 = IT_O % NSLOT, S1 = (IT_O + 1) % NSLOT, S2 = (IT_O + 2) % NSLOT;
        uint32_t a0[10][4], a1[10][4], a2[10][4];
        wait_item(full, IT_O);
#pragma unroll
        for (int b = 0; b < 10; b++) ldsm4t(a0[b], offw + b * 2048 + S0 * SLOT);
        wait_item(full, IT_O + 1);
#pragma unroll
        for (int b = 0; b < 10; b++) ldsm4t(a1[b], offw + b * 2048 + S1 * SLOT);
        bar_sync(B_O, N_CX);
        uint2 ob[3];
#pragma unroll
        for (int ks = 0; ks < 3; ks++) ob[ks] = reinterpret_cast<const uint2*>(smem + SM_O)[ks * 4 + t];
        const bool early = __all_sync(0xffffffffu, mbar_test(full + 8 * S2, ((IT_O + 2) / NSLOT) & 1));
        float y[10][4];
#pragma unroll
        for (int b = 0; b < 10; b++) { y[b][0] = y[b][1] = y[b][2] = y[b][3] = 0.f; }
        if (early) {
#pragma unroll
            for (int b = 0; b < 10; b++) ldsm4t(a2[b], offw + b * 2048 + S2 * SLOT);
        }
#pragma unroll
        for (int b = 0; b < 10; b++) mma16816(y[b], a0[b], ob[0].x, ob[0].y);
#pragma unroll
        for (int b = 0; b < 10; b++) mma16816(y[b], a1[b], ob[1].x, ob[1].y);
        if (!early) {
            wait_item(full, IT_O + 2);
#pragma unroll
            for (int b = 0; b < 10; b++) ldsm4t(a2[b], offw + b * 2048 + S2 * SLOT);
        }
#pragma unroll
        for (int b = 0; b < 10; b++) mma16816(y[b], a2[b], ob[2].x, ob[2].y);
        float v[5], sum[5], cnt[5];
#pragma unroll
        for (int i = 0; i < 5; i++) {
            v[i] = (t & 2) ? ((t & 1) ? y[2 * i + 1][2] : y[2 * i + 1][0]) : ((t & 1) ? y[2 * i][2] : y[2 * i][0]);
            asm volatile("atom.relaxed.gpu.global.add.v2.f32 {%0,%1}, [%2], {%3,%4};"
                         : "=f"(sum[i]), "=f"(cnt[i]) : "l"(dst + i * 16 * ACC_PITCH), "f"(v[i]), "f"(1.0f) : "memory");
        }
#pragma unroll
        for (int i = 0; i < 5; i++)
            if (cnt[i] == NCTA - 1)
                asm volatile("st.global.b16 [%0], %1;" :: "l"(po + i * 128), "h"(__bfloat16_as_ushort(__float2bfloat16_rn(sum[i] + v[i]))) : "memory");
        if (cnt[0] == NCTA - 1 && cw == 0 && lane == 0) {
            asm volatile("st.relaxed.gpu.global.b32 [%0], %1;" :: "l"(&sc->landed), "r"(0) : "memory");
            asm volatile("st.relaxed.gpu.global.b32 [%0], %1;" :: "l"(&sc->cleared), "r"(0) : "memory");
        }
    }
}

typedef CUresult (*EncodeTiledFn)(CUtensorMap*, CUtensorMapDataType, cuuint32_t, void*, const cuuint64_t*, const cuuint64_t*,
                                  const cuuint32_t*, const cuuint32_t*, CUtensorMapInterleave, CUtensorMapSwizzle,
                                  CUtensorMapL2promotion, CUtensorMapFloatOOBfill);

}

extern "C" void kernel_launch(void* const* d_in, const int* in_sizes, int n_in, void* d_out, int out_size) {
    (void)in_sizes; (void)n_in; (void)out_size;
    using namespace gqa;
    static EncodeTiledFn encode = nullptr;
    static Scratch* scratch = nullptr;
    if (!encode) {
        cudaGetSymbolAddress((void**)&scratch, g_scratch);
        void* fn = nullptr;
        cudaDriverEntryPointQueryResult qr;
        cudaGetDriverEntryPoint("cuTensorMapEncodeTiled", &fn, cudaEnableDefault, &qr);
        encode = (EncodeTiledFn)fn;
        cudaFuncSetAttribute(gqa_decode_kernel, cudaFuncAttributeMaxDynamicSharedMemorySize, SM_TOTAL);
    }
    CUtensorMap tm_wq, tm_wo;
    {
        cuuint64_t dims[2] = {QCOLS, D_MODEL}, strides[1] = {QCOLS * 2};
        cuuint32_t box[2] = {DH, 32}, es[2] = {1, 1};
        encode(&tm_wq, CU_TENSOR_MAP_DATA_TYPE_BFLOAT16, 2, d_in[3], dims, strides, box, es, CU_TENSOR_MAP_INTERLEAVE_NONE,
               CU_TENSOR_MAP_SWIZZLE_NONE, CU_TENSOR_MAP_L2_PROMOTION_NONE, CU_TENSOR_MAP_FLOAT_OOB_FILL_NONE);
    }
    {
        cuuint64_t dims[3] = {64, QCOLS, D_MODEL / 64}, strides[2] = {D_MODEL * 2, 128};
        cuuint32_t box[3] = {64, 16, D_MODEL / 64}, es[3] = {1, 1, 1};
        encode(&tm_wo, CU_TENSOR_MAP_DATA_TYPE_BFLOAT16, 3, d_in[4], dims, strides, box, es, CU_TENSOR_MAP_INTERLEAVE_NONE,
               CU_TENSOR_MAP_SWIZZLE_128B, CU_TENSOR_MAP_L2_PROMOTION_NONE, CU_TENSOR_MAP_FLOAT_OOB_FILL_NONE);
    }
    gqa_decode_kernel<<<NCTA, NTHREADS, SM_TOTAL>>>((const __nv_bfloat16*)d_in[1], (const __nv_bfloat16*)d_in[2],
                                                    (const __nv_bfloat16*)d_in[0], (__nv_bfloat16*)d_out, scratch, tm_wq, tm_wo);
}
```

```cpp
#include <cuda_runtime.h>
#include <cuda.h>
#include <cuda_bf16.h>
#include <stdint.h>

namespace gqa {

constexpr int D_MODEL = 640;
constexpr int NH      = 32;
constexpr int SK      = 8192;
constexpr int DH      = 192;
constexpr int QCOLS   = NH * DH;
constexpr int SPLIT   = 4;
constexpr int NCTA    = NH * SPLIT;
constexpr int NCW     = 4;
constexpr int W_XCHG = NCW + 1, W_COUNT = NCW + 2, W_CLEAR = NCW + 3;
constexpr int NTHREADS = (NCW + 4) * 32;
constexpr int TOK_CTA = SK / SPLIT;
constexpr int NTILE   = TOK_CTA / 64;
constexpr int ROWB    = DH * 2;
constexpr int GRP     = 16 * ROWB;
constexpr int SLOT    = NCW * GRP;
constexpr int NSLOT   = 8;
constexpr int XROWS   = D_MODEL / SPLIT;
constexpr int OROWS   = DH / SPLIT;
constexpr int WOB     = 16 * D_MODEL * 2;
constexpr int NACC    = D_MODEL / 8;
constexpr int ACC_PITCH = 512;
constexpr int IT_K = 3, IT_V = IT_K + NTILE, IT_O = IT_V + NTILE, IT_END = IT_O + 3;

constexpr int WIN_HEAD = 3, HEAD_UNTIL = NSLOT + IT_K;
constexpr int PACE_FROM = 48, PACE_KV = 640, PACE_WO = 384, PACE_MIN = 32;

constexpr int SM_RING = 0;
constexpr int SM_BARS = SM_RING + NSLOT * SLOT;
constexpr int SM_P    = SM_BARS + 128;
constexpr int SM_RED  = SM_P + NCW * NTILE * 8 * 4;
constexpr int SM_ML   = SM_RED + NCW * DH * 4;
constexpr int SM_Q    = SM_ML + 64;
constexpr int SM_O    = SM_Q + DH * 2;
constexpr int SM_TOTAL = SM_O + 128;
constexpr int B_CONS = 1, B_Q = 2, B_L = 3, B_F = 4, B_LATE = 5, B_O = 6;
constexpr int N_CX = (NCW + 1) * 32;

constexpr unsigned MBAR_LIMIT = 1u << 19, POLL_LIMIT = 1u << 22;

struct Scratch {
    float x2[NACC * ACC_PITCH];
    float x0[NCTA * DH];
    float x1[NCTA * SPLIT * OROWS];
    float xm[NCTA * SPLIT * 8];
    unsigned landed;
    unsigned pad[31];
    unsigned cleared;
};
__device__ __align__(128) Scratch g_scratch;

__device__ __forceinline__ uint32_t smem_u32(const void* p) { return (uint32_t)__cvta_generic_to_shared(p); }

__device__ __forceinline__ void mbar_init(uint32_t bar, uint32_t cnt) {
    asm volatile("mbarrier.init.shared::cta.b64 [%0], %1;" :: "r"(bar), "r"(cnt) : "memory");
}
__device__ __forceinline__ void mbar_init_fence() { asm volatile("fence.mbarrier_init.release.cluster;" ::: "memory"); }
__device__ __forceinline__ void mbar_expect_tx(uint32_t bar, uint32_t bytes) {
    asm volatile("mbarrier.arrive.expect_tx.shared::cta.b64 _, [%0], %1;" :: "r"(bar), "r"(bytes) : "memory");
}
__device__ __forceinline__ void mbar_arrive(uint32_t bar) {
    asm volatile("mbarrier.arrive.shared::cta.b64 _, [%0];" :: "r"(bar) : "memory");
}
__device__ __forceinline__ bool mbar_try(uint32_t bar, uint32_t parity) {
    uint32_t ok;
    asm volatile("{\n.reg .pred p;\nmbarrier.try_wait.parity.shared::cta.b64 p, [%1], %2;\nselp.u32 %0, 1, 0, p;\n}"
                 : "=r"(ok) : "r"(bar), "r"(parity) : "memory");
    return ok;
}
__device__ __forceinline__ bool mbar_test(uint32_t bar, uint32_t parity) {
    uint32_t ok;
    asm volatile("{\n.reg .pred p;\nmbarrier.test_wait.parity.shared::cta.b64 p, [%1], %2;\nselp.u32 %0, 1, 0, p;\n}"
                 : "=r"(ok) : "r"(bar), "r"(parity) : "memory");
    return ok;
}
__device__ __forceinline__ void mbar_wait(uint32_t bar, uint32_t parity) {
    if (mbar_try(bar, parity)) return;
    unsigned spins = 0;
    while (!mbar_try(bar, parity)) if (++spins > MBAR_LIMIT) __trap();
}
__device__ __forceinline__ void wait_item(uint32_t full, unsigned it) { mbar_wait(full + 8 * (it % NSLOT), (it / NSLOT) & 1); }

constexpr uint64_t STREAM = 0x12F0000000000000ull;
__device__ __forceinline__ void bulk_load(uint32_t dst, const void* src, uint32_t bytes, uint32_t bar) {
    asm volatile("cp.async.bulk.shared::cluster.global.mbarrier::complete_tx::bytes.L2::cache_hint [%0], [%1], %2, [%3], %4;"
                 :: "r"(dst), "l"(src), "r"(bytes), "r"(bar), "l"(STREAM) : "memory");
}
__device__ __forceinline__ void tma_2d(uint32_t dst, const CUtensorMap* tm, int c0, int c1, uint32_t bar) {
    asm volatile("cp.async.bulk.tensor.2d.shared::cluster.global.mbarrier::complete_tx::bytes.L2::cache_hint [%0], [%1, {%3, %4}], [%2], %5;"
                 :: "r"(dst), "l"(tm), "r"(bar), "r"(c0), "r"(c1), "l"(STREAM) : "memory");
}
__device__ __forceinline__ void tma_3d(uint32_t dst, const CUtensorMap* tm, int c0, int c1, int c2, uint32_t bar) {
    asm volatile("cp.async.bulk.tensor.3d.shared::cluster.global.mbarrier::complete_tx::bytes.L2::cache_hint [%0], [%1, {%3, %4, %5}], [%2], %6;"
                 :: "r"(dst), "l"(tm), "r"(bar), "r"(c0), "r"(c1), "r"(c2), "l"(STREAM) : "memory");
}
__device__ __forceinline__ void ldsm4(uint32_t (&a)[4], uint32_t addr) {
    asm volatile("ldmatrix.sync.aligned.m8n8.x4.shared.b16 {%0,%1,%2,%3}, [%4];"
                 : "=r"(a[0]), "=r"(a[1]), "=r"(a[2]), "=r"(a[3]) : "r"(addr) : "memory");
}
__device__ __forceinline__ void ldsm4t(uint32_t (&a)[4], uint32_t addr) {
    asm volatile("ldmatrix.sync.aligned.m8n8.x4.trans.shared.b16 {%0,%1,%2,%3}, [%4];"
                 : "=r"(a[0]), "=r"(a[1]), "=r"(a[2]), "=r"(a[3]) : "r"(addr) : "memory");
}
__device__ __forceinline__ void mma16816(float (&c)[4], const uint32_t (&a)[4], uint32_t b0, uint32_t b1) {
    asm volatile("mma.sync.aligned.m16n8k16.row.col.f32.bf16.bf16.f32 {%0,%1,%2,%3}, {%4,%5,%6,%7}, {%8,%9}, {%0,%1,%2,%3};"
                 : "+f"(c[0]), "+f"(c[1]), "+f"(c[2]), "+f"(c[3])
                 : "r"(a[0]), "r"(a[1]), "r"(a[2]), "r"(a[3]), "r"(b0), "r"(b1));
}
__device__ __forceinline__ void bar_sync(int id, int n) { asm volatile("bar.sync %0, %1;" :: "r"(id), "r"(n) : "memory"); }
__device__ __forceinline__ void bar_arrive(int id, int n) { asm volatile("bar.arrive %0, %1;" :: "r"(id), "r"(n) : "memory"); }
__device__ __forceinline__ void fence_gpu() { asm volatile("fence.acq_rel.gpu;" ::: "memory"); }

__device__ __forceinline__ uint32_t enc(float v) { uint32_t u = __float_as_uint(v); return u ? u : 0x80000000u; }
__device__ __forceinline__ void st_x4(float* p, float4 v) {
    asm volatile("st.relaxed.gpu.global.v4.b32 [%0], {%1,%2,%3,%4};"
                 :: "l"(p), "r"(enc(v.x)), "r"(enc(v.y)), "r"(enc(v.z)), "r"(enc(v.w)) : "memory");
}
__device__ __forceinline__ void st_zero4(float* p) {
    asm volatile("st.relaxed.gpu.global.v4.b32 [%0], {%1,%1,%1,%1};" :: "l"(p), "r"(0) : "memory");
}
__device__ __forceinline__ uint32_t ld_x(const unsigned* p) {
    uint32_t v;
    asm volatile("ld.relaxed.gpu.global.b32 %0, [%1];" : "=r"(v) : "l"(p) : "memory");
    return v;
}
__device__ __forceinline__ uint2 ld_x2(const float* p) {
    uint2 v;
    asm volatile("ld.relaxed.gpu.global.v2.b32 {%0,%1}, [%2];" : "=r"(v.x), "=r"(v.y) : "l"(p) : "memory");
    return v;
}
__device__ __forceinline__ void count(unsigned* p) { asm volatile("red.relaxed.gpu.global.add.u32 [%0], 1;" :: "l"(p) : "memory"); }
__device__ __forceinline__ uint32_t umin2(uint2 v) { return min(v.x, v.y); }
__device__ __forceinline__ float f32(uint32_t u) { return __uint_as_float(u); }
__device__ __forceinline__ float sum4(float a, float b, float c, float d) { return (a + b) + (c + d); }

__device__ __forceinline__ float bf16r(float v) { return __bfloat162float(__float2bfloat16_rn(v)); }
__device__ __forceinline__ uint32_t pack_bf16(float lo, float hi) {
    __nv_bfloat162 h = __floats2bfloat162_rn(lo, hi);
    return *reinterpret_cast<uint32_t*>(&h);
}
__device__ __forceinline__ float exp_neg(float v) {
    float r;
    asm("ex2.approx.ftz.f32 %0, %1;" : "=f"(r) : "f"(v * 1.4426950408889634f));
    return r;
}

__device__ __forceinline__ void rowsum_group(float (&acc)[12][4], uint32_t slot, const uint32_t (&off)[4], uint32_t b0, uint32_t b1) {
#pragma unroll
    for (int s = 0; s < 3; s++) {
        uint32_t a[4][4];
#pragma unroll
        for (int j = 0; j < 4; j++) ldsm4t(a[j], slot + off[j] + s * 128);
#pragma unroll
        for (int j = 0; j < 4; j++) mma16816(acc[s * 4 + j], a[j], b0, b1);
    }
}
__device__ __forceinline__ void rowsum_finish(const float (&acc)[12][4], float* red, int lane) {
    const int g = lane >> 2, t = lane & 3;
    const int from = (lane & ~3) | ((t + 3) & 3);
#pragma unroll
    for (int s = 0; s < 3; s++) {
        float val[8];
#pragma unroll
        for (int j = 0; j < 4; j++) {
            val[2 * j]     = acc[s * 4 + j][0] + acc[s * 4 + ((j + 3) & 3)][3];
            val[2 * j + 1] = acc[s * 4 + j][1] + acc[s * 4 + j][2];
        }
        float nw[4];
#pragma unroll
        for (int v = 0; v < 4; v++) nw[v] = val[v] + __shfl_xor_sync(0xffffffffu, val[v + 4], 2);
#pragma unroll
        for (int v = 0; v < 2; v++) red[64 * s + 8 * (2 * t + v) + g] = nw[v] + __shfl_sync(0xffffffffu, nw[v + 2], from);
    }
}
__device__ __forceinline__ void issue_wq(uint32_t ring, uint32_t full, const CUtensorMap* tm, int h, int r, int i) {
    mbar_expect_tx(full + 8 * i, i < 2 ? SLOT : SLOT / 2);
    tma_2d(ring + i * SLOT, tm, h * DH, r * XROWS + i * 64, full + 8 * i);
    if (i < 2) tma_2d(ring + i * SLOT + SLOT / 2, tm, h * DH, r * XROWS + i * 64 + 32, full + 8 * i);
}

__global__ void __launch_bounds__(NTHREADS, 1)
gqa_decode_kernel(const __nv_bfloat16* __restrict__ kc, const __nv_bfloat16* __restrict__ vc,
                  const __nv_bfloat16* __restrict__ x, __nv_bfloat16* __restrict__ out, Scratch* __restrict__ sc,
                  const __grid_constant__ CUtensorMap tm_wq, const __grid_constant__ CUtensorMap tm_wo) {
    extern __shared__ __align__(1024) unsigned char smem[];
    const int tid = threadIdx.x, warp = tid >> 5, lane = tid & 31;
    const int cta = blockIdx.x, h = cta >> 2, r = cta & 3;
    const uint32_t ring = smem_u32(smem) + SM_RING;
    const uint32_t full = smem_u32(smem) + SM_BARS, empty = full + NSLOT * 8;
    const unsigned char* kp = reinterpret_cast<const unsigned char*>(kc) + (size_t)cta * (TOK_CTA * ROWB);

    if (tid == 0) {
        mbar_init(full + 8 * IT_K, 1);
        mbar_init_fence();
        mbar_expect_tx(full + 8 * IT_K, SLOT);
        bulk_load(ring + IT_K * SLOT, kp, SLOT, full + 8 * IT_K);
#pragma unroll
        for (int i = 0; i < NSLOT; i++) if (i != IT_K) mbar_init(full + 8 * i, 1);
        mbar_init_fence();
        issue_wq(ring, full, &tm_wq, h, r, 0);
        issue_wq(ring, full, &tm_wq, h, r, 1);
#pragma unroll
        for (int i = 0; i < NSLOT; i++) mbar_init(empty + 8 * i, NCW + 1);
    }
    __syncthreads();
    const int g = lane >> 2, t = lane & 3;
    float* ml = reinterpret_cast<float*>(smem + SM_ML);

    if (warp == 0) {
        if (lane == 0) {
            const unsigned char* vp = reinterpret_cast<const unsigned char*>(vc) + (size_t)cta * (TOK_CTA * ROWB);
            asm volatile("prefetch.tensormap [%0];" :: "l"(&tm_wo) : "memory");
            wait_item(full, IT_K);
            issue_wq(ring, full, &tm_wq, h, r, 2);
            int landed = 0;
#pragma unroll 1
            for (int it = IT_K + 1; it < IT_END; it++) {
                const int s = (unsigned)it % NSLOT, n = it - IT_K;
                if (n >= PACE_FROM) {
                    const int need = it < IT_O ? NCTA * n + cta - PACE_KV
                                               : min(NCTA * n + cta - PACE_WO, NCTA * 2 * NTILE - PACE_MIN);
                    unsigned spins = 0;
                    while (landed < need) {
                        landed = ld_x(&sc->landed);
                        if (++spins > POLL_LIMIT) __trap();
                    }
                }
                if (it < HEAD_UNTIL) wait_item(full, it - WIN_HEAD <= IT_K ? it - WIN_HEAD - 1 : it - WIN_HEAD);
                if (it >= NSLOT) mbar_wait(empty + 8 * s, ((it / NSLOT) & 1) ^ 1);
                if (it < IT_O) {
                    mbar_expect_tx(full + 8 * s, SLOT);
                    bulk_load(ring + s * SLOT, it < IT_V ? kp + (size_t)n * SLOT : vp + (size_t)(it - IT_V) * SLOT, SLOT, full + 8 * s);
                } else {
                    mbar_expect_tx(full + 8 * s, WOB);
                    tma_3d(ring + s * SLOT, &tm_wo, 0, cta * OROWS + (it - IT_O) * 16, 0, full + 8 * s);
                }
            }
        }
        return;
    }

    if (warp == W_COUNT) {
        if (lane < IT_K) mbar_arrive(empty + 8 * lane);
#pragma unroll 1
        for (int it = IT_K; it < IT_O; it++) {
            wait_item(full, it);
            __syncwarp();
            if (lane == 0) {
                count(&sc->landed);
                mbar_arrive(empty + 8 * ((unsigned)it % NSLOT));
            }
            if (it == IT_O - 2) bar_arrive(B_LATE, 64);
        }
        return;
    }

    if (warp == W_XCHG) {
        {
            const float* in = sc->x0 + h * SPLIT * DH + 2 * lane;
            uint2 v[SPLIT][3];
            unsigned spins = 0, lo;
            do {
                lo = 0xffffffffu;
#pragma unroll
                for (int s = 0; s < SPLIT; s++)
#pragma unroll
                    for (int i = 0; i < 3; i++) v[s][i] = ld_x2(in + s * DH + i * 64);
#pragma unroll
                for (int s = 0; s < SPLIT; s++)
#pragma unroll
                    for (int i = 0; i < 3; i++) lo = min(lo, umin2(v[s][i]));
                if (++spins > POLL_LIMIT) __trap();
            } while (lo == 0);
            uint32_t* qw = reinterpret_cast<uint32_t*>(smem + SM_Q);
#pragma unroll
            for (int i = 0; i < 3; i++)
                qw[i * 32 + lane] = pack_bf16(sum4(f32(v[0][i].x), f32(v[1][i].x), f32(v[2][i].x), f32(v[3][i].x)),
                                              sum4(f32(v[0][i].y), f32(v[1][i].y), f32(v[2][i].y), f32(v[3][i].y)));
            bar_arrive(B_Q, N_CX);
        }
        {
            unsigned spins = 0;
            while (ld_x(&sc->cleared) < NCTA) if (++spins > POLL_LIMIT) __trap();
            fence_gpu();
        }
        {
            bar_sync(B_L, N_CX);
            const float m = fmaxf(fmaxf(ml[0], ml[1]), fmaxf(ml[2], ml[3]));
            const float l = sum4(ml[4], ml[5], ml[6], ml[7]);
            if (lane < 2 * SPLIT) st_x4(sc->xm + ((h * SPLIT + (lane >> 1)) * SPLIT + r) * 8 + (lane & 1) * 4, make_float4(m, l, m, l));
            const float* in = sc->xm + (cta * SPLIT + (lane & 3)) * 8;
            uint2 v;
            unsigned spins = 0;
            do {
                v = ld_x2(in);
                if (++spins > POLL_LIMIT) __trap();
            } while (umin2(v) == 0);
            __syncwarp();
            float mm = fmaxf(f32(v.x), __shfl_xor_sync(0xffffffffu, f32(v.x), 1));
            mm = fmaxf(mm, __shfl_xor_sync(0xffffffffu, mm, 2));
            float ll = f32(v.y) * exp_neg(f32(v.x) - mm);
            ll += __shfl_xor_sync(0xffffffffu, ll, 1);
            ll += __shfl_xor_sync(0xffffffffu, ll, 2);
            if (lane == 0) ml[8] = exp_neg(m - mm) / ll;
            bar_arrive(B_F, N_CX);
            fence_gpu();
            st_zero4(sc->x0 + cta * DH + lane * 4);
            if (lane < 16) st_zero4(sc->x0 + cta * DH + 128 + lane * 4);
        }
        {
            bar_sync(B_LATE, 64);
            const int j = lane < 24 ? lane : 0;
            const float* in = sc->x1 + cta * SPLIT * OROWS + 2 * j;
            uint2 v[SPLIT];
            unsigned spins = 0;
            do {
#pragma unroll
                for (int s = 0; s < SPLIT; s++) v[s] = ld_x2(in + s * OROWS);
                if (++spins > POLL_LIMIT) __trap();
            } while (min(min(umin2(v[0]), umin2(v[1])), min(umin2(v[2]), umin2(v[3]))) == 0);
            if (lane < 24)
                reinterpret_cast<uint32_t*>(smem + SM_O)[(j >> 3) * 8 + (j & 3) * 2 + ((j >> 2) & 1)] =
                    pack_bf16(sum4(f32(v[0].x), f32(v[1].x), f32(v[2].x), f32(v[3].x)), sum4(f32(v[0].y), f32(v[1].y), f32(v[2].y), f32(v[3].y)));
            bar_arrive(B_O, N_CX);
        }
        return;
    }

    if (warp == W_CLEAR) {
        st_zero4(sc->x1 + cta * SPLIT * OROWS + lane * 4);
        if (lane < 16) st_zero4(sc->x1 + cta * SPLIT * OROWS + 128 + lane * 4);
        if (lane < 2 * SPLIT) st_zero4(sc->xm + cta * SPLIT * 8 + lane * 4);
        if (cta < NACC && lane < 4) st_zero4(sc->x2 + cta * ACC_PITCH + lane * 4);
        __syncwarp();
        if (lane == 0) {
            fence_gpu();
            count(&sc->cleared);
        }
        return;
    }

    const int cw = warp - 1;
    const bool diag = (t == (g >> 1));
    const uint32_t sel0 = diag ? ((g & 1) ? 0x1044u : 0x4410u) : 0x4444u;
    const uint32_t sel1 = diag ? ((g & 1) ? 0x3244u : 0x4432u) : 0x4444u;
    uint32_t offk[4], offv[4];
    {
        const int mi = lane >> 3, rr = lane & 7;
#pragma unroll
        for (int j = 0; j < 4; j++) {
            offk[j] = cw * GRP + (rr + 8 * (mi & 1)) * ROWB + ((2 * j + (mi >> 1) + rr) & 7) * 16;
            offv[j] = cw * GRP + (rr + 8 * (mi >> 1)) * ROWB + ((2 * j + (mi & 1) + rr) & 7) * 16;
        }
    }
    float* red = reinterpret_cast<float*>(smem + SM_RED);
    uint32_t* pw = reinterpret_cast<uint32_t*>(smem + SM_P) + cw * (NTILE * 8);
    auto release = [&](int s) { __syncwarp(); if (lane == 0) mbar_arrive(empty + 8 * s); };

    float acc[12][4];
    {
        const int nq = cw < 2 ? 3 : 2;
        uint32_t xw[3];
#pragma unroll
        for (int i = 0; i < 3; i++) {
            xw[i] = 0;
            if (i < nq) {
                const unsigned short* xs = reinterpret_cast<const unsigned short*>(x) + r * XROWS + (cw + 4 * i) * 16 + g;
                xw[i] = (uint32_t)__ldg(xs) | ((uint32_t)__ldg(xs + 8) << 16);
            }
        }
#pragma unroll
        for (int i = 0; i < 12; i++) { acc[i][0] = acc[i][1] = acc[i][2] = acc[i][3] = 0.f; }
#pragma unroll 1
        for (int i = 0; i < 3; i++) {
            const uint32_t w = i == 0 ? xw[0] : (i == 1 ? xw[1] : xw[2]);
            wait_item(full, i);
            if (i < nq) rowsum_group(acc, ring + i * SLOT, offv, __byte_perm(w, 0, sel0), __byte_perm(w, 0, sel1));
            release(i);
        }
        rowsum_finish(acc, red + cw * DH, lane);
        bar_sync(B_CONS, NCW * 32);
        if (lane < 12) {
            const float4* r4 = reinterpret_cast<const float4*>(red) + cw * 12 + lane;
            const float4 a = r4[0], b = r4[DH / 4], c = r4[2 * DH / 4], d = r4[3 * DH / 4];
            st_x4(sc->x0 + cta * DH + cw * OROWS + lane * 4,
                  make_float4(sum4(a.x, b.x, c.x, d.x), sum4(a.y, b.y, c.y, d.y), sum4(a.z, b.z, c.z, d.z), sum4(a.w, b.w, c.w, d.w)));
        }
        bar_sync(B_Q, N_CX);
    }

    float mx = -INFINITY;
    {
        const uint32_t* qw = reinterpret_cast<const uint32_t*>(smem + SM_Q);
        uint32_t qb[3][8];
#pragma unroll
        for (int s = 0; s < 3; s++)
#pragma unroll
            for (int u = 0; u < 8; u++) qb[s][u] = qw[32 * s + 4 * ((u + g) & 7) + t];
        const float scale = 0.07216878364870322f;
#pragma unroll 1
        for (int i = 0; i < NTILE; i++) {
            const int slot = (unsigned)(IT_K + i) % NSLOT;
            wait_item(full, IT_K + i);
            const uint32_t sa = ring + slot * SLOT;
            float c[3][4];
#pragma unroll
            for (int s = 0; s < 3; s++) {
                uint32_t a[4][4];
                c[s][0] = c[s][1] = c[s][2] = c[s][3] = 0.f;
#pragma unroll
                for (int j = 0; j < 4; j++) ldsm4(a[j], sa + offk[j] + s * 128);
#pragma unroll
                for (int j = 0; j < 4; j++) mma16816(c[s], a[j], qb[s][2 * j], qb[s][2 * j + 1]);
            }
            release(slot);
            const bool odd = g & 1;
            float lo = odd ? (c[0][1] + c[1][1]) + c[2][1] : (c[0][0] + c[1][0]) + c[2][0];
            float hi = odd ? (c[0][3] + c[1][3]) + c[2][3] : (c[0][2] + c[1][2]) + c[2][2];
            lo = bf16r(bf16r(lo) * scale);
            hi = bf16r(bf16r(hi) * scale);
            if (diag) {
                mx = fmaxf(mx, fmaxf(lo, hi));
                pw[i * 8 + g] = pack_bf16(lo, hi);
            }
        }
    }
    {
#pragma unroll
        for (int o = 16; o > 0; o >>= 1) mx = fmaxf(mx, __shfl_xor_sync(0xffffffffu, mx, o));
        if (lane == 0) ml[cw] = mx;
        bar_sync(B_CONS, NCW * 32);
        mx = fmaxf(fmaxf(ml[0], ml[1]), fmaxf(ml[2], ml[3]));
        float lsum = 0.f;
#pragma unroll
        for (int i = 0; i < NTILE * 8 / 32; i++) {
            const uint32_t w = pw[i * 32 + lane];
            const float e0 = exp_neg(f32(w << 16) - mx), e1 = exp_neg(f32(w & 0xffff0000u) - mx);
            lsum += e0 + e1;
            pw[i * 32 + lane] = pack_bf16(e0, e1);
        }
#pragma unroll
        for (int o = 16; o > 0; o >>= 1) lsum += __shfl_xor_sync(0xffffffffu, lsum, o);
        if (lane == 0) ml[4 + cw] = lsum;
        __syncwarp();
        bar_arrive(B_L, N_CX);
    }
#pragma unroll
    for (int i = 0; i < 12; i++) { acc[i][0] = acc[i][1] = acc[i][2] = acc[i][3] = 0.f; }
#pragma unroll 1
    for (int i = 0; i < NTILE; i++) {
        const int slot = (unsigned)(IT_V + i) % NSLOT;
        const uint32_t w = pw[i * 8 + g];
        wait_item(full, IT_V + i);
        rowsum_group(acc, ring + slot * SLOT, offv, __byte_perm(w, 0, sel0), __byte_perm(w, 0, sel1));
        release(slot);
    }
    rowsum_finish(acc, red + cw * DH, lane);
    bar_sync(B_F, N_CX);
    if (lane < 12) {
        const float f = ml[8];
        const float4* r4 = reinterpret_cast<const float4*>(red) + cw * 12 + lane;
        const float4 a = r4[0], b = r4[DH / 4], c = r4[2 * DH / 4], d = r4[3 * DH / 4];
        st_x4(sc->x1 + ((h * SPLIT + cw) * SPLIT + r) * OROWS + lane * 4,
              make_float4(sum4(a.x, b.x, c.x, d.x) * f, sum4(a.y, b.y, c.y, d.y) * f, sum4(a.z, b.z, c.z, d.z) * f, sum4(a.w, b.w, c.w, d.w) * f));
    }
    __syncwarp();
    {
        uint32_t offw = ring + ((lane & 7) + 8 * (lane >> 4)) * 128 + (((2 * cw + ((lane >> 3) & 1)) ^ (lane & 7)) * 16);
        const int u0 = 8 * (t >> 1) + 2 * cw + (t & 1);
        float* dst = sc->x2 + u0 * ACC_PITCH + 2 * g;
        __nv_bfloat16* po = out + u0 * 8 + g;
        asm volatile("" : "+r"(offw), "+l"(dst), "+l"(po));
        constexpr int S0 = IT_O % NSLOT, S1 = (IT_O + 1) % NSLOT, S2 = (IT_O + 2) % NSLOT;
        uint32_t a0[10][4], a1[10][4], a2[10][4];
        wait_item(full, IT_O);
#pragma unroll
        for (int b = 0; b < 10; b++) ldsm4t(a0[b], offw + b * 2048 + S0 * SLOT);
        wait_item(full, IT_O + 1);
#pragma unroll
        for (int b = 0; b < 10; b++) ldsm4t(a1[b], offw + b * 2048 + S1 * SLOT);
        bar_sync(B_O, N_CX);
        uint2 ob[3];
#pragma unroll
        for (int ks = 0; ks < 3; ks++) ob[ks] = reinterpret_cast<const uint2*>(smem + SM_O)[ks * 4 + t];
        const bool early = __all_sync(0xffffffffu, mbar_test(full + 8 * S2, ((IT_O + 2) / NSLOT) & 1));
        float y[10][4];
#pragma unroll
        for (int b = 0; b < 10; b++) { y[b][0] = y[b][1] = y[b][2] = y[b][3] = 0.f; }
        if (early) {
#pragma unroll
            for (int b = 0; b < 10; b++) ldsm4t(a2[b], offw + b * 2048 + S2 * SLOT);
        }
#pragma unroll
        for (int b = 0; b < 10; b++) mma16816(y[b], a0[b], ob[0].x, ob[0].y);
#pragma unroll
        for (int b = 0; b < 10; b++) mma16816(y[b], a1[b], ob[1].x, ob[1].y);
        if (!early) {
            wait_item(full, IT_O + 2);
#pragma unroll
            for (int b = 0; b < 10; b++) ldsm4t(a2[b], offw + b * 2048 + S2 * SLOT);
        }
#pragma unroll
        for (int b = 0; b < 10; b++) mma16816(y[b], a2[b], ob[2].x, ob[2].y);
        float v[5], sum[5], cnt[5];
#pragma unroll
        for (int i = 0; i < 5; i++) {
            v[i] = (t & 2) ? ((t & 1) ? y[2 * i + 1][2] : y[2 * i + 1][0]) : ((t & 1) ? y[2 * i][2] : y[2 * i][0]);
            asm volatile("atom.relaxed.gpu.global.add.v2.f32 {%0,%1}, [%2], {%3,%4};"
                         : "=f"(sum[i]), "=f"(cnt[i]) : "l"(dst + i * 16 * ACC_PITCH), "f"(v[i]), "f"(1.0f) : "memory");
        }
#pragma unroll
        for (int i = 0; i < 5; i++)
            if (cnt[i] == NCTA - 1)
                asm volatile("st.global.b16 [%0], %1;" :: "l"(po + i * 128), "h"(__bfloat16_as_ushort(__float2bfloat16_rn(sum[i] + v[i]))) : "memory");
        if (cnt[0] == NCTA - 1 && cw == 0 && lane == 0) {
            asm volatile("st.relaxed.gpu.global.b32 [%0], %1;" :: "l"(&sc->landed), "r"(0) : "memory");
            asm volatile("st.relaxed.gpu.global.b32 [%0], %1;" :: "l"(&sc->cleared), "r"(0) : "memory");
        }
    }
}

typedef CUresult (*EncodeTiledFn)(CUtensorMap*, CUtensorMapDataType, cuuint32_t, void*, const cuuint64_t*, const cuuint64_t*,
                                  const cuuint32_t*, const cuuint32_t*, CUtensorMapInterleave, CUtensorMapSwizzle,
                                  CUtensorMapL2promotion, CUtensorMapFloatOOBfill);

}

extern "C" void kernel_launch(void* const* d_in, const int* in_sizes, int n_in, void* d_out, int out_size) {
    (void)in_sizes; (void)n_in; (void)out_size;
    using namespace gqa;
    static EncodeTiledFn encode = nullptr;
    static Scratch* scratch = nullptr;
    if (!encode) {
        cudaGetSymbolAddress((void**)&scratch, g_scratch);
        void* fn = nullptr;
        cudaDriverEntryPointQueryResult qr;
        cudaGetDriverEntryPoint("cuTensorMapEncodeTiled", &fn, cudaEnableDefault, &qr);
        encode = (EncodeTiledFn)fn;
        cudaFuncSetAttribute(gqa_decode_kernel, cudaFuncAttributeMaxDynamicSharedMemorySize, SM_TOTAL);
    }
    CUtensorMap tm_wq, tm_wo;
    {
        cuuint64_t dims[2] = {QCOLS, D_MODEL}, strides[1] = {QCOLS * 2};
        cuuint32_t box[2] = {DH, 32}, es[2] = {1, 1};
        encode(&tm_wq, CU_TENSOR_MAP_DATA_TYPE_BFLOAT16, 2, d_in[3], dims, strides, box, es, CU_TENSOR_MAP_INTERLEAVE_NONE,
               CU_TENSOR_MAP_SWIZZLE_NONE, CU_TENSOR_MAP_L2_PROMOTION_NONE, CU_TENSOR_MAP_FLOAT_OOB_FILL_NONE);
    }
    {
        cuuint64_t dims[3] = {64, QCOLS, D_MODEL / 64}, strides[2] = {D_MODEL * 2, 128};
        cuuint32_t box[3] = {64, 16, D_MODEL / 64}, es[3] = {1, 1, 1};
        encode(&tm_wo, CU_TENSOR_MAP_DATA_TYPE_BFLOAT16, 3, d_in[4], dims, strides, box, es, CU_TENSOR_MAP_INTERLEAVE_NONE,
               CU_TENSOR_MAP_SWIZZLE_128B, CU_TENSOR_MAP_L2_PROMOTION_NONE, CU_TENSOR_MAP_FLOAT_OOB_FILL_NONE);
    }
    cudaLaunchAttribute attr;
    attr.id = cudaLaunchAttributeCooperative;
    attr.val.cooperative = 1;
    cudaLaunchConfig_t cfg = {};
    cfg.gridDim = dim3(NCTA);
    cfg.blockDim = dim3(NTHREADS);
    cfg.dynamicSmemBytes = SM_TOTAL;
    cfg.stream = cudaStreamPerThread;
    cfg.attrs = &attr;
    cfg.numAttrs = 1;
    cudaLaunchKernelEx(&cfg, gqa_decode_kernel, (const __nv_bfloat16*)d_in[1], (const __nv_bfloat16*)d_in[2],
                       (const __nv_bfloat16*)d_in[0], (__nv_bfloat16*)d_out, scratch, tm_wq, tm_wo);
}
```
